```python
import torch

def _softmax(x, axis=-1):
    return torch.softmax(x, dim=axis)
def _gelu(x):
    return torch.nn.functional.gelu(x, approximate="tanh")
def _silu(x):
    return torch.nn.functional.silu(x)
def _sigmoid(x):
    return torch.sigmoid(x)
def _layernorm(x, axis=-1, eps=1e-5):
    m = x.mean(dim=axis, keepdim=True)
    v = x.var(dim=axis, keepdim=True, unbiased=False)
    return (x - m) / torch.sqrt(v + eps)
def _scatter_add(tgt, idx, src, axis=0):
    return tgt.clone().index_add_(axis, idx, src)
def _segment_sum(src, seg, n):
    out = torch.zeros((n,) + src.shape[1:], dtype=src.dtype)
    return out.index_add_(0, seg, src)
def _pad(x, pw):
    flat = tuple(v for pair in reversed(pw) for v in pair)
    return torch.nn.functional.pad(x, flat)

kernel_name = 'concat_heads__gqa_block_cached__mha_block_cached__decode'

def setup_inputs():

    _w = (lambda a: (lambda t: t.to(torch.bfloat16) if t.is_floating_point() else t)(torch.as_tensor(a)))
    def _A_setup():
        B, Sq, D = 2, 1, 640
        Hq, Hkv, Sk, Dh = 32, 32, 8192, 192
        assert Hq % Hkv == 0, (Hq, Hkv)
        return {
            "x": _w((lambda *s: torch.randn(*s, dtype=torch.bfloat16) * 0.8)(B, Sq, D)),
            "k_cache": _w((lambda *s: torch.randn(*s, dtype=torch.bfloat16) * 0.8)(B, Hkv, Sk, Dh)),
            "v_cache": _w((lambda *s: torch.randn(*s, dtype=torch.bfloat16) * 0.05)(B, Hkv, Sk, Dh)),
            "wq": _w((lambda *s: torch.randn(*s, dtype=torch.bfloat16) * 0.8)(D, Hq * Dh) * (D ** -0.5)),
            "wo": _w((lambda *s: torch.randn(*s, dtype=torch.bfloat16) * 0.05)(Hq * Dh, D) * ((Hq * Dh) ** -0.5)),
        }
    _A_in = _A_setup()

    def _B_setup():
        B, Sq, D = 2, 1, 640
        H, Sk, Dh = 32, 8192, 192
        return {
            "x": _w((lambda *s: torch.randn(*s, dtype=torch.bfloat16) * 0.8)(B, Sq, D)),
            "k_cache": _w((lambda *s: torch.randn(*s, dtype=torch.bfloat16) * 0.8)(B, H, Sk, Dh)),
            "v_cache": _w((lambda *s: torch.randn(*s, dtype=torch.bfloat16) * 0.05)(B, H, Sk, Dh)),
            "wq": _w((lambda *s: torch.randn(*s, dtype=torch.bfloat16) * 0.8)(D, H * Dh) * (D ** -0.5)),
            "wo": _w((lambda *s: torch.randn(*s, dtype=torch.bfloat16) * 0.05)(H * Dh, D) * ((H * Dh) ** -0.5)),
        }
    _B_in = _B_setup()

    return {
        "A_x": _A_in["x"],
        "A_k_cache": _A_in["k_cache"],
        "A_v_cache": _A_in["v_cache"],
        "A_wq": _A_in["wq"],
        "A_wo": _A_in["wo"],
        "B_x": _B_in["x"],
        "B_k_cache": _B_in["k_cache"],
        "B_v_cache": _B_in["v_cache"],
        "B_wq": _B_in["wq"],
        "B_wo": _B_in["wo"],
    }

def reference(A_x, A_k_cache, A_v_cache, A_wq, A_wo, B_x, B_k_cache, B_v_cache, B_wq, B_wo):
    def _A_ref(x, k_cache, v_cache, wq, wo):
        B, Sq, D = x.shape
        Hq, Dh = 32, 192
        Hkv = k_cache.shape[1]
        rep = Hq // Hkv
        q = (lambda x, *d: x.permute(*d))((x @ wq).reshape(B, Sq, Hq, Dh), 0, 2, 1, 3)
        k = (lambda x, n, axis: torch.repeat_interleave(x, n, dim=axis))(k_cache, rep, axis=1)
        v = (lambda x, n, axis: torch.repeat_interleave(x, n, dim=axis))(v_cache, rep, axis=1)
        scores = torch.einsum("bhqd,bhkd->bhqk", q, k) * (Dh ** -0.5)
        p = _softmax(scores, axis=-1)
        o = torch.einsum("bhqk,bhkd->bhqd", p, v)
        return (lambda x, *d: x.permute(*d))(o, 0, 2, 1, 3).reshape(B, Sq, Hq * Dh) @ wo

    def _B_ref(x, k_cache, v_cache, wq, wo):
        B, Sq, D = x.shape
        H, Dh = 32, 192
        q = (lambda x, *d: x.permute(*d))((x @ wq).reshape(B, Sq, H, Dh), 0, 2, 1, 3)
        scores = torch.einsum("bhqd,bhkd->bhqk", q, k_cache) * (Dh ** -0.5)
        p = _softmax(scores, axis=-1)
        o = torch.einsum("bhqk,bhkd->bhqd", p, v_cache)
        return (lambda x, *d: x.permute(*d))(o, 0, 2, 1, 3).reshape(B, Sq, H * Dh) @ wo

    a = _A_ref(A_x, A_k_cache, A_v_cache, A_wq, A_wo)
    b = _B_ref(B_x, B_k_cache, B_v_cache, B_wq, B_wo)
    return torch.concatenate([a, b], axis=-1)
```

```cpp
#include <cuda_runtime.h>
#include <cuda_bf16.h>
#include <cuda.h>
#include <stdint.h>
#include <stdio.h>

namespace {

constexpr int DM = 640;
constexpr int NH = 32;
constexpr int SK = 8192;
constexpr int DH = 192;

constexpr int NSLOT      = 8;
constexpr int SLOT_BYTES = 24576;
constexpr int N_WQ   = 5;
constexpr int N_PAIR = SK / 64;
constexpr int N_WO   = 6;
constexpr int T_KV0  = N_WQ;
constexpr int T_WO0  = N_WQ + 2 * N_PAIR;
constexpr int N_TILES = T_WO0 + N_WO;
constexpr int WO_BYTES = 32 * 640;

constexpr int NCONS_THREADS = 256;
constexpr int NTHREADS = 288;

constexpr int QP_STRIDE_B = 208;
constexpr int OFF_RING  = 0;
constexpr int OFF_PART  = NSLOT * SLOT_BYTES;
constexpr int OFF_QOWN  = OFF_PART + 8 * 2 * QP_STRIDE_B * 4;
constexpr int OFF_QPEER = OFF_QOWN + DH * 4;
constexpr int OFF_OBUF  = OFF_QPEER + DH * 4;
constexpr int OFF_ML    = OFF_OBUF + 2 * DH * 2;
constexpr int OFF_BARS  = OFF_ML + 8 * 2 * 4;
constexpr int OFF_EPOCH = OFF_BARS + (2 * NSLOT + 2) * 8;
constexpr int SMEM_USED = OFF_EPOCH + 16;
constexpr int SMEM_BYTES = SMEM_USED + 1024;

struct alignas(64) Params {
    CUtensorMap k[2];
    CUtensorMap v[2];
    CUtensorMap wq[2];
    CUtensorMap wo[2];
    const __nv_bfloat16* x[2];
    __nv_bfloat16* out;
};

__device__ unsigned long long g_part[2 * 2 * NH * 640];
__device__ unsigned int g_epoch[4];

constexpr unsigned SPIN_LIMIT = 1u << 24;

__device__ __forceinline__ uint32_t smem_u32(const void* p) { return (uint32_t)__cvta_generic_to_shared(p); }

__device__ __forceinline__ void mbar_init(uint32_t bar, uint32_t cnt) {
    asm volatile("mbarrier.init.shared::cta.b64 [%0], %1;" ::"r"(bar), "r"(cnt) : "memory");
}
__device__ __forceinline__ void mbar_expect_tx(uint32_t bar, uint32_t bytes) {
    asm volatile("mbarrier.arrive.expect_tx.shared::cta.b64 _, [%0], %1;" ::"r"(bar), "r"(bytes) : "memory");
}
__device__ __forceinline__ void mbar_arrive(uint32_t bar) {
    asm volatile("mbarrier.arrive.shared::cta.b64 _, [%0];" ::"r"(bar) : "memory");
}
__device__ __forceinline__ bool mbar_try(uint32_t bar, uint32_t parity) {
    uint32_t ok;
    asm volatile("{\n.reg .pred p;\nmbarrier.try_wait.parity.shared::cta.b64 p, [%1], %2;\nselp.u32 %0, 1, 0, p;\n}"
                 : "=r"(ok) : "r"(bar), "r"(parity) : "memory");
    return ok != 0;
}
__device__ __forceinline__ bool mbar_try_cluster(uint32_t bar, uint32_t parity) {
    uint32_t ok;
    asm volatile("{\n.reg .pred p;\nmbarrier.try_wait.parity.acquire.cluster.shared::cta.b64 p, [%1], %2;\nselp.u32 %0, 1, 0, p;\n}"
                 : "=r"(ok) : "r"(bar), "r"(parity) : "memory");
    return ok != 0;
}
__device__ __forceinline__ void mbar_wait(uint32_t bar, uint32_t parity) {
    unsigned n = 0;
    while (!mbar_try(bar, parity)) { if (++n > SPIN_LIMIT) __trap(); }
}
__device__ __forceinline__ void mbar_wait_cluster(uint32_t bar, uint32_t parity) {
    unsigned n = 0;
    while (!mbar_try_cluster(bar, parity)) { if (++n > SPIN_LIMIT) __trap(); }
}
__device__ __forceinline__ void tma2d(uint32_t dst, const CUtensorMap* tm, int c0, int c1, uint32_t bar, uint64_t pol) {
    asm volatile("cp.async.bulk.tensor.2d.shared::cluster.global.mbarrier::complete_tx::bytes.L2::cache_hint"
                 " [%0], [%1, {%3, %4}], [%2], %5;"
                 ::"r"(dst), "l"(tm), "r"(bar), "r"(c0), "r"(c1), "l"(pol) : "memory");
}
__device__ __forceinline__ void tma3d(uint32_t dst, const CUtensorMap* tm, int c0, int c1, int c2, uint32_t bar, uint64_t pol) {
    asm volatile("cp.async.bulk.tensor.3d.shared::cluster.global.mbarrier::complete_tx::bytes.L2::cache_hint"
                 " [%0], [%1, {%3, %4, %5}], [%2], %6;"
                 ::"r"(dst), "l"(tm), "r"(bar), "r"(c0), "r"(c1), "r"(c2), "l"(pol) : "memory");
}
__device__ __forceinline__ void ldsm4(uint32_t (&a)[4], uint32_t addr) {
    asm volatile("ldmatrix.sync.aligned.m8n8.x4.shared.b16 {%0,%1,%2,%3}, [%4];"
                 : "=r"(a[0]), "=r"(a[1]), "=r"(a[2]), "=r"(a[3]) : "r"(addr) : "memory");
}
__device__ __forceinline__ void ldsm4t(uint32_t (&a)[4], uint32_t addr) {
    asm volatile("ldmatrix.sync.aligned.m8n8.x4.trans.shared.b16 {%0,%1,%2,%3}, [%4];"
                 : "=r"(a[0]), "=r"(a[1]), "=r"(a[2]), "=r"(a[3]) : "r"(addr) : "memory");
}
__device__ __forceinline__ void mma16816(float (&c)[4], const uint32_t (&a)[4], uint32_t b0, uint32_t b1) {
    asm volatile("mma.sync.aligned.m16n8k16.row.col.f32.bf16.bf16.f32 {%0,%1,%2,%3}, {%4,%5,%6,%7}, {%8,%9}, {%0,%1,%2,%3};"
                 : "+f"(c[0]), "+f"(c[1]), "+f"(c[2]), "+f"(c[3])
                 : "r"(a[0]), "r"(a[1]), "r"(a[2]), "r"(a[3]), "r"(b0), "r"(b1));
}
__device__ __forceinline__ float ex2(float x) {
    float y;
    asm("ex2.approx.ftz.f32 %0, %1;" : "=f"(y) : "f"(x));
    return y;
}
__device__ __forceinline__ uint32_t pack_bf16(float lo, float hi) {
    uint32_t r;
    asm("cvt.rn.bf16x2.f32 %0, %1, %2;" : "=r"(r) : "f"(hi), "f"(lo));
    return r;
}
__device__ __forceinline__ uint32_t mapa(uint32_t addr, uint32_t cta) {
    uint32_t r;
    asm("mapa.shared::cluster.u32 %0, %1, %2;" : "=r"(r) : "r"(addr), "r"(cta));
    return r;
}
__device__ __forceinline__ void st_async_b32(uint32_t raddr, uint32_t v, uint32_t rbar) {
    asm volatile("st.async.weak.shared::cluster.mbarrier::complete_tx::bytes.b32 [%0], %1, [%2];"
                 ::"r"(raddr), "r"(v), "r"(rbar) : "memory");
}
__device__ __forceinline__ void cons_sync() { asm volatile("bar.sync 1, 256;" ::: "memory"); }
__device__ __forceinline__ void cluster_arrive() { asm volatile("barrier.cluster.arrive.release.aligned;" ::: "memory"); }
__device__ __forceinline__ void cluster_wait() { asm volatile("barrier.cluster.wait.acquire.aligned;" ::: "memory"); }

__device__ __forceinline__ void pv_step(float (&acc)[12][4], uint32_t tile_addr, const uint32_t (&voff)[3],
                                        uint32_t b0, uint32_t b1) {
#pragma unroll
    for (int mt = 0; mt < 12; ++mt) {
        uint32_t a[4];
        ldsm4t(a, (tile_addr + voff[mt >> 2]) ^ ((mt & 3) << 5));
        mma16816(acc[mt], a, b0, b1);
    }
}

__global__ void __cluster_dims__(2, 1, 1) __launch_bounds__(NTHREADS, 1)
fused_decode_kernel(const __grid_constant__ Params p) {
    extern __shared__ uint8_t smem_raw[];
    const uint32_t sbase = (smem_u32(smem_raw) + 1023u) & ~1023u;
    uint8_t* sgen = smem_raw + (sbase - smem_u32(smem_raw));

    const int tid  = threadIdx.x;
    const int warp = tid >> 5;
    const int lane = tid & 31;
    const int r    = blockIdx.x & 1;
    const int cl   = blockIdx.x >> 1;
    const int br   = cl >> 5;
    const int h    = cl & 31;

    const uint32_t ring  = sbase + OFF_RING;
    const uint32_t fullb = sbase + OFF_BARS;
    const uint32_t emptb = fullb + NSLOT * 8;
    const uint32_t xqb   = emptb + NSLOT * 8;
    const uint32_t xob   = xqb + 8;

    if (warp == 8) {
        uint64_t pol = 0;
        const int kv_line0 = (r * NH + h) * SK * 3;
        auto issue = [&](int i) {
            const int s = i & (NSLOT - 1);
            const uint32_t dst = ring + s * SLOT_BYTES;
            const uint32_t bar = fullb + s * 8;
            if (i < T_KV0) {
                mbar_expect_tx(bar, SLOT_BYTES);
                tma3d(dst, &p.wq[br], 0, 3 * h, 320 * r + 64 * i, bar, pol);
            } else if (i < T_WO0) {
                const int j = i - T_KV0;
                mbar_expect_tx(bar, SLOT_BYTES);
                tma2d(dst, (j & 1) ? &p.v[br] : &p.k[br], 0, kv_line0 + (j >> 1) * 192, bar, pol);
            } else {
                mbar_expect_tx(bar, WO_BYTES);
                tma3d(dst, &p.wo[br], 0, 5 * r, DH * h + 32 * (i - T_WO0), bar, pol);
            }
        };
        if (lane == 0) {
            for (int s = 0; s < NSLOT; ++s) { mbar_init(fullb + s * 8, 1); mbar_init(emptb + s * 8, 4); }
            mbar_init(xqb, 1);
            mbar_init(xob, 1);
            asm volatile("fence.mbarrier_init.release.cluster;" ::: "memory");
            asm volatile("createpolicy.fractional.L2::evict_first.b64 %0, 1.0;" : "=l"(pol));
            for (int i = 0; i < NSLOT; ++i) issue(i);
            mbar_expect_tx(xqb, DH * 4);
            mbar_expect_tx(xob, DH * 2);
        }
        __syncwarp();
        cluster_arrive();
        cluster_wait();
        if (lane == 0) {
            for (int i = NSLOT; i < N_TILES; ++i) {
                mbar_wait(emptb + (i & (NSLOT - 1)) * 8, ((i >> 3) & 1) ^ 1);
                issue(i);
            }
        }
    } else {
        const int g  = lane >> 2;
        const int t  = lane & 3;
        const int gs = warp >> 2;
        const int wi = warp & 3;
        const int grp = br * 2 + r;

        uint32_t xb[3][2];
        {
            const uint32_t* xw = reinterpret_cast<const uint32_t*>(p.x[br] + (g & 1) * DM + 320 * r + 16 * wi + 2 * t);
#pragma unroll
            for (int ii = 0; ii < 3; ++ii) {
                const int i = gs + 2 * ii;
                if (i < N_WQ) { xb[ii][0] = __ldg(xw + 32 * i); xb[ii][1] = __ldg(xw + 32 * i + 4); }
                else { xb[ii][0] = 0; xb[ii][1] = 0; }
            }
        }
        unsigned epoch = 0;
        if (tid == 0) epoch = *reinterpret_cast<volatile unsigned*>(&g_epoch[grp]);

        uint32_t koff[3], voff[3];
        {
            const int rowk = 16 * wi + (lane & 7) + 8 * ((lane >> 3) & 1), hik = lane >> 4;
            const int rowv = 16 * wi + (lane & 7) + 8 * (lane >> 4),       hiv = (lane >> 3) & 1;
#pragma unroll
            for (int sg = 0; sg < 3; ++sg) {
                const int lk = 3 * rowk + sg, lv = 3 * rowv + sg;
                koff[sg] = lk * 128 + ((hik ^ (lk & 7)) << 4);
                voff[sg] = lv * 128 + ((hiv ^ (lv & 7)) << 4);
            }
        }

        cluster_arrive();
        cluster_wait();

        float acc[12][4];
#pragma unroll
        for (int mt = 0; mt < 12; ++mt) { acc[mt][0] = acc[mt][1] = acc[mt][2] = acc[mt][3] = 0.f; }

#pragma unroll
        for (int ii = 0; ii < 3; ++ii) {
            const int i = gs + 2 * ii;
            if (i < N_WQ) {
                mbar_wait(fullb + i * 8, 0);
                pv_step(acc, ring + i * SLOT_BYTES, voff, xb[ii][0], xb[ii][1]);
                __syncwarp();
                if (lane == 0) mbar_arrive(emptb + i * 8);
            }
        }
        float* part = reinterpret_cast<float*>(sgen + OFF_PART);
        float* qown = reinterpret_cast<float*>(sgen + OFF_QOWN);
        float* qpeer = reinterpret_cast<float*>(sgen + OFF_QPEER);
        {
            float* dst = part + (warp * 2 + (t & 1)) * QP_STRIDE_B + g + 8 * (t >> 1);
#pragma unroll
            for (int mt = 0; mt < 12; ++mt) {
                const float v = (t == 0) ? acc[mt][0] : (t == 1) ? acc[mt][1] : (t == 2) ? acc[mt][2] : acc[mt][3];
                dst[16 * mt] = v;
            }
            if (tid == 0) *reinterpret_cast<unsigned*>(sgen + OFF_EPOCH) = epoch;
        }
        cons_sync();
        if (tid < DH) {
            float own = 0.f, oth = 0.f;
#pragma unroll
            for (int w = 0; w < 8; ++w) {
                own += part[(w * 2 + r) * QP_STRIDE_B + tid];
                oth += part[(w * 2 + (r ^ 1)) * QP_STRIDE_B + tid];
            }
            qown[tid] = own;
            st_async_b32(mapa(sbase + OFF_QPEER + tid * 4, r ^ 1), __float_as_uint(oth), mapa(xqb, r ^ 1));
        }
        cons_sync();
        mbar_wait_cluster(xqb, 0);
        epoch = *reinterpret_cast<volatile unsigned*>(sgen + OFF_EPOCH);

        uint32_t qb[12][2];
#pragma unroll
        for (int s = 0; s < 12; ++s) {
            const int c = 16 * s + 2 * t;
            qb[s][0] = pack_bf16(qown[c] + qpeer[c], qown[c + 1] + qpeer[c + 1]);
            qb[s][1] = pack_bf16(qown[c + 8] + qpeer[c + 8], qown[c + 9] + qpeer[c + 9]);
        }

#pragma unroll
        for (int mt = 0; mt < 12; ++mt) { acc[mt][0] = acc[mt][1] = acc[mt][2] = acc[mt][3] = 0.f; }
        const float sc = 0.07216878364870322f * 1.4426950408889634f;
        float m = -INFINITY, l = 0.f;

#pragma unroll 1
        for (int jj = 0; jj < N_PAIR / 2; ++jj) {
            const int iK = T_KV0 + 2 * (2 * jj + gs);
            const int iV = iK + 1;
            const int sK = iK & (NSLOT - 1), sV = iV & (NSLOT - 1);

            mbar_wait(fullb + sK * 8, (iK >> 3) & 1);
            float cA[4] = {0.f, 0.f, 0.f, 0.f}, cB[4] = {0.f, 0.f, 0.f, 0.f};
            {
                const uint32_t kt = ring + sK * SLOT_BYTES;
#pragma unroll
                for (int s = 0; s < 12; s += 2) {
                    uint32_t a0[4], a1[4];
                    ldsm4(a0, (kt + koff[s >> 2]) ^ ((s & 3) << 5));
                    ldsm4(a1, (kt + koff[(s + 1) >> 2]) ^ (((s + 1) & 3) << 5));
                    mma16816(cA, a0, qb[s][0], qb[s][1]);
                    mma16816(cB, a1, qb[s + 1][0], qb[s + 1][1]);
                }
            }
            __syncwarp();
            if (lane == 0) mbar_arrive(emptb + sK * 8);

            const float s0 = cA[0] + cB[0];
            const float s1 = cA[2] + cB[2];
            float bm = fmaxf(s0, s1);
            bm = fmaxf(bm, __shfl_xor_sync(0xffffffffu, bm, 4));
            bm = fmaxf(bm, __shfl_xor_sync(0xffffffffu, bm, 8));
            bm = fmaxf(bm, __shfl_xor_sync(0xffffffffu, bm, 16));
            if (bm > m) {
                const float f = ex2((m - bm) * sc);
                l *= f;
#pragma unroll
                for (int mt = 0; mt < 12; ++mt) { acc[mt][0] *= f; acc[mt][2] *= f; }
                m = bm;
            }
            const float ms = m * sc;
            const float p0 = ex2(fmaf(s0, sc, -ms));
            const float p1 = ex2(fmaf(s1, sc, -ms));
            l += p0 + p1;
            const uint32_t pk = pack_bf16(p0, p1);
            const uint32_t u = __shfl_sync(0xffffffffu, pk, 8 * t);
            const uint32_t v = __shfl_sync(0xffffffffu, pk, 8 * t + 4);
            const uint32_t b0 = __byte_perm(u, v, 0x5410);
            const uint32_t b1 = __byte_perm(u, v, 0x7632);

            mbar_wait(fullb + sV * 8, (iV >> 3) & 1);
            pv_step(acc, ring + sV * SLOT_BYTES, voff, b0, b1);
            __syncwarp();
            if (lane == 0) mbar_arrive(emptb + sV * 8);
        }

        l += __shfl_xor_sync(0xffffffffu, l, 4);
        l += __shfl_xor_sync(0xffffffffu, l, 8);
        l += __shfl_xor_sync(0xffffffffu, l, 16);
        float* ml = reinterpret_cast<float*>(sgen + OFF_ML);
        if (t == 0) {
            float* dst = part + warp * DH + g;
#pragma unroll
            for (int mt = 0; mt < 12; ++mt) { dst[16 * mt] = acc[mt][0]; dst[16 * mt + 8] = acc[mt][2]; }
            if (lane == 0) { ml[warp * 2] = m; ml[warp * 2 + 1] = l; }
        }
        cons_sync();
        uint32_t* obuf = reinterpret_cast<uint32_t*>(sgen + OFF_OBUF);
        if (tid < DH / 2) {
            float M = ml[0];
#pragma unroll
            for (int w = 1; w < 8; ++w) M = fmaxf(M, ml[2 * w]);
            float L = 0.f, o0 = 0.f, o1 = 0.f;
#pragma unroll
            for (int w = 0; w < 8; ++w) {
                const float f = ex2((ml[2 * w] - M) * sc);
                L = fmaf(f, ml[2 * w + 1], L);
                const float2 pv = *reinterpret_cast<const float2*>(part + w * DH + 2 * tid);
                o0 = fmaf(f, pv.x, o0);
                o1 = fmaf(f, pv.y, o1);
            }
            const float inv = 1.0f / L;
            const uint32_t ob = pack_bf16(o0 * inv, o1 * inv);
            obuf[r * 96 + tid] = ob;
            st_async_b32(mapa(sbase + OFF_OBUF + (r * 96 + tid) * 4, r ^ 1), ob, mapa(xob, r ^ 1));
        }
        cons_sync();
        mbar_wait_cluster(xob, 0);

        float oc[3][4];
#pragma unroll
        for (int q = 0; q < 3; ++q) { oc[q][0] = oc[q][1] = oc[q][2] = oc[q][3] = 0.f; }
        {
            const int rr0 = (lane & 7) + 8 * (lane >> 4), hi = (lane >> 3) & 1;
            const uint32_t* ob = obuf + (g & 1) * 96 + t;
#pragma unroll
            for (int i = 0; i < N_WO; ++i) {
                const int it = T_WO0 + i;
                const int s = it & (NSLOT - 1);
                mbar_wait(fullb + s * 8, (it >> 3) & 1);
                const uint32_t tile = ring + s * SLOT_BYTES;
#pragma unroll
                for (int kk = 0; kk < 2; ++kk) {
                    const uint32_t b0 = ob[8 * (2 * i + kk)], b1 = ob[8 * (2 * i + kk) + 4];
                    const int rr = 16 * kk + rr0;
#pragma unroll
                    for (int q = 0; q < 3; ++q) {
                        const int mt = warp + 8 * q;
                        if (mt < 20) {
                            const int line = 5 * rr + (mt >> 2);
                            const int ch = (2 * (mt & 3) + hi) ^ (line & 7);
                            uint32_t a[4];
                            ldsm4t(a, tile + line * 128 + (ch << 4));
                            mma16816(oc[q], a, b0, b1);
                        }
                    }
                }
            }
        }
        const unsigned tag = epoch + 1u;
        {
            unsigned long long* dst = g_part + (size_t)(grp * NH + h) * 640 + (t & 1) * 320 + g + 8 * (t >> 1);
#pragma unroll
            for (int q = 0; q < 3; ++q) {
                const int mt = warp + 8 * q;
                if (mt < 20) {
                    const float v = (t == 0) ? oc[q][0] : (t == 1) ? oc[q][1] : (t == 2) ? oc[q][2] : oc[q][3];
                    const unsigned long long w = ((unsigned long long)tag << 32) | __float_as_uint(v);
                    asm volatile("st.relaxed.gpu.global.b64 [%0], %1;" ::"l"(dst + 16 * mt), "l"(w) : "memory");
                }
            }
        }
        if (tid < 160) {
            const int j = tid >> 3, s = tid & 7;
            const int o = 20 * h + j;
            const unsigned long long* src = g_part + (size_t)(grp * NH + 4 * s) * 640 + o;
            float v[4];
#pragma unroll
            for (int i = 0; i < 4; ++i) {
                unsigned long long w;
                unsigned n = 0;
                while (true) {
                    asm volatile("ld.relaxed.gpu.global.b64 %0, [%1];" : "=l"(w) : "l"(src + i * 640) : "memory");
                    if ((unsigned)(w >> 32) == tag) break;
                    if (++n > SPIN_LIMIT) __trap();
                }
                v[i] = __uint_as_float((unsigned)w);
            }
            float sum = (v[0] + v[1]) + (v[2] + v[3]);
            sum += __shfl_xor_sync(0xffffffffu, sum, 1);
            sum += __shfl_xor_sync(0xffffffffu, sum, 2);
            sum += __shfl_xor_sync(0xffffffffu, sum, 4);
            if (s == 0) {
                const int b = o / 320, col = o - b * 320;
                p.out[b * (2 * DM) + br * DM + r * 320 + col] = __float2bfloat16(sum);
            }
            if (h == 0 && tid == 0) *reinterpret_cast<volatile unsigned*>(&g_epoch[grp]) = tag;
        }
    }
}

typedef CUresult (*EncodeTiledFn)(CUtensorMap*, CUtensorMapDataType, cuuint32_t, void*, const cuuint64_t*,
                                  const cuuint64_t*, const cuuint32_t*, const cuuint32_t*, CUtensorMapInterleave,
                                  CUtensorMapSwizzle, CUtensorMapL2promotion, CUtensorMapFloatOOBfill);

bool encode(EncodeTiledFn fn, CUtensorMap* tm, const void* ptr, int rank, const cuuint64_t* dims,
            const cuuint64_t* strides, const cuuint32_t* box) {
    const cuuint32_t es[3] = {1, 1, 1};
    CUresult rc = fn(tm, CU_TENSOR_MAP_DATA_TYPE_BFLOAT16, (cuuint32_t)rank, const_cast<void*>(ptr), dims, strides, box, es,
                     CU_TENSOR_MAP_INTERLEAVE_NONE, CU_TENSOR_MAP_SWIZZLE_128B, CU_TENSOR_MAP_L2_PROMOTION_L2_128B,
                     CU_TENSOR_MAP_FLOAT_OOB_FILL_NONE);
    if (rc != CUDA_SUCCESS) { fprintf(stderr, "cuTensorMapEncodeTiled failed: %d\n", (int)rc); return false; }
    return true;
}

}

extern "C" void kernel_launch(void* const* d_in, const int* in_sizes, int n_in, void* d_out, int out_size) {
    (void)in_sizes; (void)n_in; (void)out_size;
    static EncodeTiledFn fn = nullptr;
    if (!fn) {
        void* f = nullptr;
        cudaDriverEntryPointQueryResult qr;
        if (cudaGetDriverEntryPoint("cuTensorMapEncodeTiled", &f, cudaEnableDefault, &qr) != cudaSuccess || !f) {
            fprintf(stderr, "cuTensorMapEncodeTiled not available\n");
            return;
        }
        fn = (EncodeTiledFn)f;
        cudaFuncSetAttribute(fused_decode_kernel, cudaFuncAttributeMaxDynamicSharedMemorySize, SMEM_BYTES);
    }
    Params p;
    for (int b = 0; b < 2; ++b) {
        void* const* in = d_in + 5 * b;
        p.x[b] = (const __nv_bfloat16*)in[0];
        {
            const cuuint64_t dims[2] = {64, (cuuint64_t)2 * NH * SK * 3};
            const cuuint64_t strides[1] = {128};
            const cuuint32_t box[2] = {64, 192};
            if (!encode(fn, &p.k[b], in[1], 2, dims, strides, box)) return;
            if (!encode(fn, &p.v[b], in[2], 2, dims, strides, box)) return;
        }
        {
            const cuuint64_t dims[3] = {64, 96, 640};
            const cuuint64_t strides[2] = {128, 12288};
            const cuuint32_t box[3] = {64, 3, 64};
            if (!encode(fn, &p.wq[b], in[3], 3, dims, strides, box)) return;
        }
        {
            const cuuint64_t dims[3] = {64, 10, 6144};
            const cuuint64_t strides[2] = {128, 1280};
            const cuuint32_t box[3] = {64, 5, 32};
            if (!encode(fn, &p.wo[b], in[4], 3, dims, strides, box)) return;
        }
    }
    p.out = (__nv_bfloat16*)d_out;
    fused_decode_kernel<<<128, NTHREADS, SMEM_BYTES>>>(p);
}
```

```cpp
#include <cuda_runtime.h>
#include <cuda_bf16.h>
#include <cuda.h>
#include <stdint.h>
#include <stdio.h>

namespace {

constexpr int DM = 640;
constexpr int NH = 32;
constexpr int SK = 8192;
constexpr int DH = 192;

constexpr int NSLOT      = 8;
constexpr int SLOT_BYTES = 24576;
constexpr int N_WQ   = 5;
constexpr int N_PAIR = SK / 64;
constexpr int N_WO   = 6;
constexpr int T_KV0  = N_WQ;
constexpr int T_WO0  = N_WQ + 2 * N_PAIR;
constexpr int N_TILES = T_WO0 + N_WO;
constexpr int WO_BYTES = 32 * 640;

constexpr int NTHREADS = 288;

constexpr int QP_STRIDE_B = 208;
constexpr int OB_STRIDE = 112;
constexpr int OFF_RING  = 0;
constexpr int OFF_PART  = NSLOT * SLOT_BYTES;
constexpr int OFF_QOWN  = OFF_PART + 8 * 2 * QP_STRIDE_B * 4;
constexpr int OFF_QPEER = OFF_QOWN + DH * 4;
constexpr int OFF_OBUF  = OFF_QPEER + DH * 4;
constexpr int OFF_ML    = OFF_OBUF + 2 * OB_STRIDE * 4;
constexpr int OFF_BARS  = OFF_ML + 8 * 2 * 4;
constexpr int OFF_EPOCH = OFF_BARS + (2 * NSLOT + 2 + N_WO) * 8;
constexpr int SMEM_USED = OFF_EPOCH + 16;
constexpr int SMEM_BYTES = SMEM_USED + 1024;

struct alignas(64) Params {
    CUtensorMap k[2];
    CUtensorMap v[2];
    CUtensorMap wq[2];
    CUtensorMap wo[2];
    const __nv_bfloat16* x[2];
    __nv_bfloat16* out;
};

__device__ unsigned long long g_part[2 * 2 * NH * 640];
__device__ unsigned int g_epoch[4];
__device__ unsigned int g_done[4];

constexpr unsigned SPIN_LIMIT = 1u << 24;

#define TS(i) do { } while (0)

__device__ __forceinline__ uint32_t smem_u32(const void* p) { return (uint32_t)__cvta_generic_to_shared(p); }

__device__ __forceinline__ void mbar_init(uint32_t bar, uint32_t cnt) {
    asm volatile("mbarrier.init.shared::cta.b64 [%0], %1;" ::"r"(bar), "r"(cnt) : "memory");
}
__device__ __forceinline__ void mbar_expect_tx(uint32_t bar, uint32_t bytes) {
    asm volatile("mbarrier.arrive.expect_tx.shared::cta.b64 _, [%0], %1;" ::"r"(bar), "r"(bytes) : "memory");
}
__device__ __forceinline__ void mbar_arrive(uint32_t bar) {
    asm volatile("mbarrier.arrive.shared::cta.b64 _, [%0];" ::"r"(bar) : "memory");
}
__device__ __forceinline__ bool mbar_try(uint32_t bar, uint32_t parity) {
    uint32_t ok;
    asm volatile("{\n.reg .pred p;\nmbarrier.try_wait.parity.shared::cta.b64 p, [%1], %2;\nselp.u32 %0, 1, 0, p;\n}"
                 : "=r"(ok) : "r"(bar), "r"(parity) : "memory");
    return ok != 0;
}
__device__ __forceinline__ bool mbar_try_cluster(uint32_t bar, uint32_t parity) {
    uint32_t ok;
    asm volatile("{\n.reg .pred p;\nmbarrier.try_wait.parity.acquire.cluster.shared::cta.b64 p, [%1], %2;\nselp.u32 %0, 1, 0, p;\n}"
                 : "=r"(ok) : "r"(bar), "r"(parity) : "memory");
    return ok != 0;
}
__device__ __forceinline__ void mbar_wait(uint32_t bar, uint32_t parity) {
    unsigned n = 0;
    while (!mbar_try(bar, parity)) { if (++n > SPIN_LIMIT) __trap(); }
}
__device__ __forceinline__ void mbar_wait_cluster(uint32_t bar, uint32_t parity) {
    unsigned n = 0;
    while (!mbar_try_cluster(bar, parity)) { if (++n > SPIN_LIMIT) __trap(); }
}
__device__ __forceinline__ void tma2d(uint32_t dst, const CUtensorMap* tm, int c0, int c1, uint32_t bar, uint64_t pol) {
    asm volatile("cp.async.bulk.tensor.2d.shared::cluster.global.mbarrier::complete_tx::bytes.L2::cache_hint"
                 " [%0], [%1, {%3, %4}], [%2], %5;"
                 ::"r"(dst), "l"(tm), "r"(bar), "r"(c0), "r"(c1), "l"(pol) : "memory");
}
__device__ __forceinline__ void tma3d(uint32_t dst, const CUtensorMap* tm, int c0, int c1, int c2, uint32_t bar, uint64_t pol) {
    asm volatile("cp.async.bulk.tensor.3d.shared::cluster.global.mbarrier::complete_tx::bytes.L2::cache_hint"
                 " [%0], [%1, {%3, %4, %5}], [%2], %6;"
                 ::"r"(dst), "l"(tm), "r"(bar), "r"(c0), "r"(c1), "r"(c2), "l"(pol) : "memory");
}
__device__ __forceinline__ void ldsm4(uint32_t (&a)[4], uint32_t addr) {
    asm volatile("ldmatrix.sync.aligned.m8n8.x4.shared.b16 {%0,%1,%2,%3}, [%4];"
                 : "=r"(a[0]), "=r"(a[1]), "=r"(a[2]), "=r"(a[3]) : "r"(addr) : "memory");
}
__device__ __forceinline__ void ldsm4t(uint32_t (&a)[4], uint32_t addr) {
    asm volatile("ldmatrix.sync.aligned.m8n8.x4.trans.shared.b16 {%0,%1,%2,%3}, [%4];"
                 : "=r"(a[0]), "=r"(a[1]), "=r"(a[2]), "=r"(a[3]) : "r"(addr) : "memory");
}
__device__ __forceinline__ void mma16816(float (&c)[4], const uint32_t (&a)[4], uint32_t b0, uint32_t b1) {
    asm volatile("mma.sync.aligned.m16n8k16.row.col.f32.bf16.bf16.f32 {%0,%1,%2,%3}, {%4,%5,%6,%7}, {%8,%9}, {%0,%1,%2,%3};"
                 : "+f"(c[0]), "+f"(c[1]), "+f"(c[2]), "+f"(c[3])
                 : "r"(a[0]), "r"(a[1]), "r"(a[2]), "r"(a[3]), "r"(b0), "r"(b1));
}
__device__ __forceinline__ float ex2(float x) {
    float y;
    asm("ex2.approx.ftz.f32 %0, %1;" : "=f"(y) : "f"(x));
    return y;
}
__device__ __forceinline__ float rcp(float x) {
    float y;
    asm("rcp.approx.ftz.f32 %0, %1;" : "=f"(y) : "f"(x));
    return y;
}
__device__ __forceinline__ uint32_t pack_bf16(float lo, float hi) {
    uint32_t r;
    asm("cvt.rn.bf16x2.f32 %0, %1, %2;" : "=r"(r) : "f"(hi), "f"(lo));
    return r;
}
__device__ __forceinline__ uint32_t mapa(uint32_t addr, uint32_t cta) {
    uint32_t r;
    asm("mapa.shared::cluster.u32 %0, %1, %2;" : "=r"(r) : "r"(addr), "r"(cta));
    return r;
}
__device__ __forceinline__ void st_async_b32(uint32_t raddr, uint32_t v, uint32_t rbar) {
    asm volatile("st.async.weak.shared::cluster.mbarrier::complete_tx::bytes.b32 [%0], %1, [%2];"
                 ::"r"(raddr), "r"(v), "r"(rbar) : "memory");
}
__device__ __forceinline__ void cons_sync() { asm volatile("bar.sync 1, 256;" ::: "memory"); }
__device__ __forceinline__ void part_arrive() { asm volatile("bar.arrive 2, 288;" ::: "memory"); }
__device__ __forceinline__ void part_sync() { asm volatile("bar.sync 2, 288;" ::: "memory"); }
__device__ __forceinline__ float sel4(int t, float a, float b, float c, float d) {
    const float lo = (t & 1) ? b : a, hi = (t & 1) ? d : c;
    return (t & 2) ? hi : lo;
}
__device__ __forceinline__ void cluster_arrive() { asm volatile("barrier.cluster.arrive.relaxed.aligned;" ::: "memory"); }
__device__ __forceinline__ void cluster_wait() { asm volatile("barrier.cluster.wait.acquire.aligned;" ::: "memory"); }

__device__ __forceinline__ void pv_step(float (&acc)[12][4], uint32_t tile_addr, const uint32_t (&voff)[3],
                                        uint32_t b0, uint32_t b1) {
#pragma unroll
    for (int mt = 0; mt < 12; ++mt) {
        uint32_t a[4];
        ldsm4t(a, (tile_addr + voff[mt >> 2]) ^ ((mt & 3) << 5));
        mma16816(acc[mt], a, b0, b1);
    }
}

__global__ void __cluster_dims__(2, 1, 1) __launch_bounds__(NTHREADS, 1)
fused_decode_kernel(const __grid_constant__ Params p) {
    extern __shared__ uint8_t smem_raw[];
    const uint32_t sbase = (smem_u32(smem_raw) + 1023u) & ~1023u;
    uint8_t* sgen = smem_raw + (sbase - smem_u32(smem_raw));

    const int tid  = threadIdx.x;
    const int warp = tid >> 5;
    const int lane = tid & 31;
    const int r    = blockIdx.x & 1;
    const int cl   = blockIdx.x >> 1;
    const int br   = cl >> 5;
    const int h    = cl & 31;

    const uint32_t ring  = sbase + OFF_RING;
    const uint32_t fullb = sbase + OFF_BARS;
    const uint32_t emptb = fullb + NSLOT * 8;
    const uint32_t xqb   = emptb + NSLOT * 8;
    const uint32_t xob   = xqb + 8;
    const uint32_t wob   = xob + 8;

    if (warp == 8) {
        uint64_t pol = 0;
        const int kv_line0 = (r * NH + h) * SK * 3;
        auto issue = [&](int i) {
            const int s = i & (NSLOT - 1);
            const uint32_t dst = ring + s * SLOT_BYTES;
            const uint32_t bar = fullb + s * 8;
            if (i < T_KV0) {
                mbar_expect_tx(bar, SLOT_BYTES);
                tma3d(dst, &p.wq[br], 0, 3 * h, 320 * r + 64 * i, bar, pol);
            } else if (i < T_WO0) {
                const int j = i - T_KV0;
                mbar_expect_tx(bar, SLOT_BYTES);
                tma2d(dst, (j & 1) ? &p.v[br] : &p.k[br], 0, kv_line0 + (j >> 1) * 192, bar, pol);
            } else {
                const uint32_t wb = wob + (i - T_WO0) * 8;
                mbar_expect_tx(wb, WO_BYTES);
                tma3d(dst, &p.wo[br], 0, 5 * r, DH * h + 32 * (i - T_WO0), wb, pol);
            }
        };
        if (lane == 0) {
            TS(0);
            for (int s = 0; s < NSLOT; ++s) { mbar_init(fullb + s * 8, 1); mbar_init(emptb + s * 8, 4); }
            mbar_init(xqb, 1);
            mbar_init(xob, 2);
            for (int k = 0; k < N_WO; ++k) mbar_init(wob + k * 8, 1);
            asm volatile("fence.mbarrier_init.release.cluster;" ::: "memory");
            asm volatile("createpolicy.fractional.L2::evict_first.b64 %0, 1.0;" : "=l"(pol));
            for (int i = 0; i < NSLOT; ++i) issue(i);
            mbar_expect_tx(xqb, DH * 4);
            mbar_expect_tx(xob, DH * 2);
        }
        __syncwarp();
        cluster_arrive();
        cluster_wait();
        if (lane == 0) {
            for (int i = NSLOT; i < N_TILES; ++i) {
                mbar_wait(emptb + (i & (NSLOT - 1)) * 8, ((i >> 3) & 1) ^ 1);
                issue(i);
            }
        }
        __syncwarp();
        {
            const float* part = reinterpret_cast<const float*>(sgen + OFF_PART);
            const float* ml   = reinterpret_cast<const float*>(sgen + OFF_ML);
            uint32_t* obuf    = reinterpret_cast<uint32_t*>(sgen + OFF_OBUF);
            const float sc = 0.07216878364870322f * 1.4426950408889634f;
            const int u = lane & 7;
            const int pos0 = r * OB_STRIDE + 16 * (lane >> 4) + 4 * (u & 3) + 2 * ((lane >> 3) & 1) + (u >> 2);
            const uint32_t ra = mapa(sbase + OFF_OBUF + pos0 * 4, r ^ 1), rb = mapa(xob, r ^ 1);
            part_sync();
            const float4 ml0 = *reinterpret_cast<const float4*>(ml), ml1 = *reinterpret_cast<const float4*>(ml + 4);
            const float4 ml2 = *reinterpret_cast<const float4*>(ml + 8), ml3 = *reinterpret_cast<const float4*>(ml + 12);
            float2 pv[8][3];
#pragma unroll
            for (int w = 0; w < 8; ++w)
#pragma unroll
                for (int k = 0; k < 3; ++k) pv[w][k] = *reinterpret_cast<const float2*>(part + w * DH + 2 * (lane + 32 * k));
            const float mw[8] = {ml0.x, ml0.z, ml1.x, ml1.z, ml2.x, ml2.z, ml3.x, ml3.z};
            const float lw[8] = {ml0.y, ml0.w, ml1.y, ml1.w, ml2.y, ml2.w, ml3.y, ml3.w};
            const float M = fmaxf(fmaxf(fmaxf(mw[0], mw[1]), fmaxf(mw[2], mw[3])), fmaxf(fmaxf(mw[4], mw[5]), fmaxf(mw[6], mw[7])));
            float L = 0.f, o[3][2] = {{0.f, 0.f}, {0.f, 0.f}, {0.f, 0.f}};
#pragma unroll
            for (int w = 0; w < 8; ++w) {
                const float f = ex2((mw[w] - M) * sc);
                L = fmaf(f, lw[w], L);
#pragma unroll
                for (int k = 0; k < 3; ++k) {
                    o[k][0] = fmaf(f, pv[w][k].x, o[k][0]);
                    o[k][1] = fmaf(f, pv[w][k].y, o[k][1]);
                }
            }
            const float inv = rcp(L);
#pragma unroll
            for (int k = 0; k < 3; ++k) {
                const uint32_t ob = pack_bf16(o[k][0] * inv, o[k][1] * inv);
                obuf[pos0 + 32 * k] = ob;
                st_async_b32(ra + 128 * k, ob, rb);
            }
            __syncwarp();
            if (lane == 0) { mbar_arrive(xob); TS(5); }
        }
    } else {
        const int g  = lane >> 2;
        const int t  = lane & 3;
        const int gs = warp >> 2;
        const int wi = warp & 3;
        const int grp = br * 2 + r;

        uint32_t xb[3][2];
        {
            const uint32_t* xw = reinterpret_cast<const uint32_t*>(p.x[br] + (g & 1) * DM + 320 * r + 16 * wi + 2 * t);
#pragma unroll
            for (int ii = 0; ii < 3; ++ii) {
                const int i = gs + 2 * ii;
                if (i < N_WQ) { xb[ii][0] = __ldg(xw + 32 * i); xb[ii][1] = __ldg(xw + 32 * i + 4); }
                else { xb[ii][0] = 0; xb[ii][1] = 0; }
            }
        }
        unsigned epoch = 0;
        if (tid == 0) epoch = *reinterpret_cast<volatile unsigned*>(&g_epoch[grp]);

        uint32_t koff[3], voff[3];
        {
            const int rowk = 16 * wi + (lane & 7) + 8 * ((lane >> 3) & 1), hik = lane >> 4;
            const int rowv = 16 * wi + (lane & 7) + 8 * (lane >> 4),       hiv = (lane >> 3) & 1;
#pragma unroll
            for (int sg = 0; sg < 3; ++sg) {
                const int lk = 3 * rowk + sg, lv = 3 * rowv + sg;
                koff[sg] = lk * 128 + ((hik ^ (lk & 7)) << 4);
                voff[sg] = lv * 128 + ((hiv ^ (lv & 7)) << 4);
            }
        }

        cluster_arrive();
        cluster_wait();

        float acc[12][4];
#pragma unroll
        for (int mt = 0; mt < 12; ++mt) { acc[mt][0] = acc[mt][1] = acc[mt][2] = acc[mt][3] = 0.f; }

#pragma unroll
        for (int ii = 0; ii < 3; ++ii) {
            const int i = gs + 2 * ii;
            if (i < N_WQ) {
                mbar_wait(fullb + i * 8, 0);
                if (lane == 0 && wi == 0 && (i == 0 || i == 4)) TS(i == 0 ? 1 : 2);
                pv_step(acc, ring + i * SLOT_BYTES, voff, xb[ii][0], xb[ii][1]);
                __syncwarp();
                if (lane == 0) mbar_arrive(emptb + i * 8);
            }
        }
        float* part = reinterpret_cast<float*>(sgen + OFF_PART);
        float* qown = reinterpret_cast<float*>(sgen + OFF_QOWN);
        float* qpeer = reinterpret_cast<float*>(sgen + OFF_QPEER);
        {
            float* dst = part + (warp * 2 + (t & 1)) * QP_STRIDE_B + g + 8 * (t >> 1);
#pragma unroll
            for (int mt = 0; mt < 12; ++mt) {
                const float v = sel4(t, acc[mt][0], acc[mt][1], acc[mt][2], acc[mt][3]);
                dst[16 * mt] = v;
            }
            if (tid == 0) *reinterpret_cast<unsigned*>(sgen + OFF_EPOCH) = epoch;
        }
        cons_sync();
        if (tid < DH) {
            float own = 0.f, oth = 0.f;
#pragma unroll
            for (int w = 0; w < 8; ++w) {
                own += part[(w * 2 + r) * QP_STRIDE_B + tid];
                oth += part[(w * 2 + (r ^ 1)) * QP_STRIDE_B + tid];
            }
            qown[tid] = own;
            st_async_b32(mapa(sbase + OFF_QPEER + tid * 4, r ^ 1), __float_as_uint(oth), mapa(xqb, r ^ 1));
        }
        cons_sync();
        mbar_wait_cluster(xqb, 0);
        epoch = *reinterpret_cast<volatile unsigned*>(sgen + OFF_EPOCH);

        uint32_t qb[12][2];
#pragma unroll
        for (int s = 0; s < 12; ++s) {
            const int c = 16 * s + 2 * t;
            qb[s][0] = pack_bf16(qown[c] + qpeer[c], qown[c + 1] + qpeer[c + 1]);
            qb[s][1] = pack_bf16(qown[c + 8] + qpeer[c + 8], qown[c + 9] + qpeer[c + 9]);
        }

        if (tid == 0) TS(3);
#pragma unroll
        for (int mt = 0; mt < 12; ++mt) { acc[mt][0] = acc[mt][1] = acc[mt][2] = acc[mt][3] = 0.f; }
        const float sc = 0.07216878364870322f * 1.4426950408889634f;
        float m = -INFINITY, l = 0.f;

#pragma unroll 1
        for (int jj = 0; jj < N_PAIR / 2; ++jj) {
            const int iK = T_KV0 + 2 * (2 * jj + gs);
            const int iV = iK + 1;
            const int sK = iK & (NSLOT - 1), sV = iV & (NSLOT - 1);

            mbar_wait(fullb + sK * 8, (iK >> 3) & 1);
            float cA[4] = {0.f, 0.f, 0.f, 0.f}, cB[4] = {0.f, 0.f, 0.f, 0.f};
            {
                const uint32_t kt = ring + sK * SLOT_BYTES;
#pragma unroll
                for (int s = 0; s < 12; s += 2) {
                    uint32_t a0[4], a1[4];
                    ldsm4(a0, (kt + koff[s >> 2]) ^ ((s & 3) << 5));
                    ldsm4(a1, (kt + koff[(s + 1) >> 2]) ^ (((s + 1) & 3) << 5));
                    mma16816(cA, a0, qb[s][0], qb[s][1]);
                    mma16816(cB, a1, qb[s + 1][0], qb[s + 1][1]);
                }
            }
            __syncwarp();
            if (lane == 0) mbar_arrive(emptb + sK * 8);

            const float s0 = cA[0] + cB[0];
            const float s1 = cA[2] + cB[2];
            float bm = fmaxf(s0, s1);
            bm = fmaxf(bm, __shfl_xor_sync(0xffffffffu, bm, 4));
            bm = fmaxf(bm, __shfl_xor_sync(0xffffffffu, bm, 8));
            bm = fmaxf(bm, __shfl_xor_sync(0xffffffffu, bm, 16));
            if (bm > m) {
                const float f = ex2((m - bm) * sc);
                l *= f;
#pragma unroll
                for (int mt = 0; mt < 12; ++mt) { acc[mt][0] *= f; acc[mt][2] *= f; }
                m = bm;
            }
            const float ms = m * sc;
            const float p0 = ex2(fmaf(s0, sc, -ms));
            const float p1 = ex2(fmaf(s1, sc, -ms));
            l += p0 + p1;
            const uint32_t pk = pack_bf16(p0, p1);
            const uint32_t u = __shfl_sync(0xffffffffu, pk, 8 * t);
            const uint32_t v = __shfl_sync(0xffffffffu, pk, 8 * t + 4);
            const uint32_t b0 = __byte_perm(u, v, 0x5410);
            const uint32_t b1 = __byte_perm(u, v, 0x7632);

            mbar_wait(fullb + sV * 8, (iV >> 3) & 1);
            pv_step(acc, ring + sV * SLOT_BYTES, voff, b0, b1);
            __syncwarp();
            if (lane == 0) mbar_arrive(emptb + sV * 8);
        }

        if (tid == 128) {
            TS(4);
            asm volatile("red.relaxed.gpu.global.add.u32 [%0], 1;" ::"l"(&g_done[grp]) : "memory");
        }
        l += __shfl_xor_sync(0xffffffffu, l, 4);
        l += __shfl_xor_sync(0xffffffffu, l, 8);
        l += __shfl_xor_sync(0xffffffffu, l, 16);
        float* ml = reinterpret_cast<float*>(sgen + OFF_ML);
        if (t < 2) {
            float* dst = part + warp * DH + g + 8 * t;
#pragma unroll
            for (int mt = 0; mt < 12; ++mt) dst[16 * mt] = t ? acc[mt][2] : acc[mt][0];
        }
        if (lane == 0) { ml[warp * 2] = m; ml[warp * 2 + 1] = l; }
        part_arrive();

        uint32_t woff[3][2];
        {
            const int rowt = (lane & 7) + 8 * (lane >> 4), hit = (lane >> 3) & 1;
#pragma unroll
            for (int q = 0; q < 3; ++q) {
                const int mt = warp + 8 * q;
#pragma unroll
                for (int kk = 0; kk < 2; ++kk) {
                    const int line = 5 * (16 * kk + rowt) + (mt >> 2);
                    woff[q][kk] = ring + line * 128 + (((2 * (mt & 3) + hit) ^ (line & 7)) << 4);
                }
            }
        }
        uint32_t wa[2][12][4];
#pragma unroll
        for (int i = 0; i < N_WO; ++i) {
            const uint32_t so = ((T_WO0 + i) & (NSLOT - 1)) * SLOT_BYTES;
            mbar_wait(wob + i * 8, 0);
#pragma unroll
            for (int q = 0; q < 2; ++q) {
                ldsm4t(wa[q][2 * i], woff[q][0] + so);
                ldsm4t(wa[q][2 * i + 1], woff[q][1] + so);
            }
        }
        mbar_wait_cluster(xob, 0);
        if (tid == 0) TS(6);

        float oc[3][2][4];
#pragma unroll
        for (int q = 0; q < 3; ++q)
#pragma unroll
            for (int kk = 0; kk < 2; ++kk) { oc[q][kk][0] = oc[q][kk][1] = oc[q][kk][2] = oc[q][kk][3] = 0.f; }
        {
            const uint32_t* obuf = reinterpret_cast<const uint32_t*>(sgen + OFF_OBUF);
            const uint4* os = reinterpret_cast<const uint4*>(obuf + (g & 1) * OB_STRIDE + 4 * t);
            uint4 b[N_WO];
#pragma unroll
            for (int i = 0; i < N_WO; ++i) b[i] = os[4 * i];
#pragma unroll
            for (int i = 0; i < N_WO; ++i)
#pragma unroll
                for (int q = 0; q < 2; ++q) {
                    mma16816(oc[q][0], wa[q][2 * i], b[i].x, b[i].y);
                    mma16816(oc[q][1], wa[q][2 * i + 1], b[i].z, b[i].w);
                }
            if (warp < 4) {
                uint32_t wb[12][4];
#pragma unroll
                for (int i = 0; i < N_WO; ++i) {
                    const uint32_t so = ((T_WO0 + i) & (NSLOT - 1)) * SLOT_BYTES;
                    ldsm4t(wb[2 * i], woff[2][0] + so);
                    ldsm4t(wb[2 * i + 1], woff[2][1] + so);
                }
#pragma unroll
                for (int i = 0; i < N_WO; ++i) {
                    mma16816(oc[2][0], wb[2 * i], b[i].x, b[i].y);
                    mma16816(oc[2][1], wb[2 * i + 1], b[i].z, b[i].w);
                }
            }
        }
        if (tid == 0) TS(7);
        const unsigned tag = epoch + 1u;
        {
#pragma unroll
            for (int q = 0; q < 3; ++q) {
                const int o = (t & 1) * 320 + 16 * (warp + 8 * q) + g + 8 * (t >> 1);
                const int red = (o * 3277) >> 16;
                unsigned long long* dst = g_part + ((size_t)(grp * NH + red) * NH + h) * 20 + (o - 20 * red);
                const float v = sel4(t, oc[q][0][0] + oc[q][1][0], oc[q][0][1] + oc[q][1][1],
                                        oc[q][0][2] + oc[q][1][2], oc[q][0][3] + oc[q][1][3]);
                const unsigned long long w = ((unsigned long long)tag << 32) | __float_as_uint(v);
                if (q < 2 || warp < 4)
                    asm volatile("st.relaxed.gpu.global.b64 [%0], %1;" ::"l"(dst), "l"(w) : "memory");
            }
        }
        if (tid == 0) TS(9);
        if (tid < 160) {
            const unsigned long long* src = g_part + (size_t)(grp * NH + h) * 640 + tid;
            float v[4] = {0.f, 0.f, 0.f, 0.f};
            {
                unsigned n = 0, c;
                bool have[4] = {false, false, false, false};
                asm volatile("ld.relaxed.gpu.global.u32 %0, [%1];" : "=r"(c) : "l"(&g_done[grp]) : "memory");
                while (true) {
                    unsigned long long w[4] = {0ull, 0ull, 0ull, 0ull};
#pragma unroll
                    for (int i = 0; i < 4; ++i)
                        if (!have[i]) asm volatile("ld.relaxed.gpu.global.b64 %0, [%1];" : "=l"(w[i]) : "l"(src + i * 160) : "memory");
#pragma unroll
                    for (int i = 0; i < 4; ++i)
                        if (!have[i] && (unsigned)(w[i] >> 32) == tag) { have[i] = true; v[i] = __uint_as_float((unsigned)w[i]); }
                    if (__all_sync(0xffffffffu, have[0] && have[1] && have[2] && have[3])) break;
                    while ((int)(c - tag * NH) < 0) {
                        __nanosleep(300);
                        asm volatile("ld.relaxed.gpu.global.u32 %0, [%1];" : "=r"(c) : "l"(&g_done[grp]) : "memory");
                        if (++n > SPIN_LIMIT) __trap();
                    }
                    if (++n > SPIN_LIMIT) __trap();
                }
            }
            float* red = reinterpret_cast<float*>(sgen + OFF_PART);
#pragma unroll
            for (int i = 0; i < 4; ++i) red[tid + 160 * i] = v[i];
            asm volatile("bar.sync 3, 160;" ::: "memory");
            const int j = tid >> 3, s = tid & 7;
            const int o = 20 * h + j;
#pragma unroll
            for (int i = 0; i < 4; ++i) v[i] = red[(4 * s + i) * 20 + j];
            float sum = (v[0] + v[1]) + (v[2] + v[3]);
            sum += __shfl_xor_sync(0xffffffffu, sum, 1);
            sum += __shfl_xor_sync(0xffffffffu, sum, 2);
            sum += __shfl_xor_sync(0xffffffffu, sum, 4);
            if (s == 0) {
                const int b = o / 320, col = o - b * 320;
                p.out[b * (2 * DM) + br * DM + r * 320 + col] = __float2bfloat16(sum);
            }
            if (tid == 0) { TS(8);
            }
            if (h == 0 && tid == 0) *reinterpret_cast<volatile unsigned*>(&g_epoch[grp]) = tag;
        }
    }
}

typedef CUresult (*EncodeTiledFn)(CUtensorMap*, CUtensorMapDataType, cuuint32_t, void*, const cuuint64_t*,
                                  const cuuint64_t*, const cuuint32_t*, const cuuint32_t*, CUtensorMapInterleave,
                                  CUtensorMapSwizzle, CUtensorMapL2promotion, CUtensorMapFloatOOBfill);

bool encode(EncodeTiledFn fn, CUtensorMap* tm, const void* ptr, int rank, const cuuint64_t* dims,
            const cuuint64_t* strides, const cuuint32_t* box) {
    const cuuint32_t es[3] = {1, 1, 1};
    CUresult rc = fn(tm, CU_TENSOR_MAP_DATA_TYPE_BFLOAT16, (cuuint32_t)rank, const_cast<void*>(ptr), dims, strides, box, es,
                     CU_TENSOR_MAP_INTERLEAVE_NONE, CU_TENSOR_MAP_SWIZZLE_128B, CU_TENSOR_MAP_L2_PROMOTION_L2_128B,
                     CU_TENSOR_MAP_FLOAT_OOB_FILL_NONE);
    if (rc != CUDA_SUCCESS) { fprintf(stderr, "cuTensorMapEncodeTiled failed: %d\n", (int)rc); return false; }
    return true;
}

}

extern "C" void kernel_launch(void* const* d_in, const int* in_sizes, int n_in, void* d_out, int out_size) {
    (void)in_sizes; (void)n_in; (void)out_size;
    static EncodeTiledFn fn = nullptr;
    if (!fn) {
        void* f = nullptr;
        cudaDriverEntryPointQueryResult qr;
        if (cudaGetDriverEntryPoint("cuTensorMapEncodeTiled", &f, cudaEnableDefault, &qr) != cudaSuccess || !f) {
            fprintf(stderr, "cuTensorMapEncodeTiled not available\n");
            return;
        }
        fn = (EncodeTiledFn)f;
        cudaFuncSetAttribute(fused_decode_kernel, cudaFuncAttributeMaxDynamicSharedMemorySize, SMEM_BYTES);
    }
    Params p;
    for (int b = 0; b < 2; ++b) {
        void* const* in = d_in + 5 * b;
        p.x[b] = (const __nv_bfloat16*)in[0];
        {
            const cuuint64_t dims[2] = {64, (cuuint64_t)2 * NH * SK * 3};
            const cuuint64_t strides[1] = {128};
            const cuuint32_t box[2] = {64, 192};
            if (!encode(fn, &p.k[b], in[1], 2, dims, strides, box)) return;
            if (!encode(fn, &p.v[b], in[2], 2, dims, strides, box)) return;
        }
        {
            const cuuint64_t dims[3] = {64, 96, 640};
            const cuuint64_t strides[2] = {128, 12288};
            const cuuint32_t box[3] = {64, 3, 64};
            if (!encode(fn, &p.wq[b], in[3], 3, dims, strides, box)) return;
        }
        {
            const cuuint64_t dims[3] = {64, 10, 6144};
            const cuuint64_t strides[2] = {128, 1280};
            const cuuint32_t box[3] = {64, 5, 32};
            if (!encode(fn, &p.wo[b], in[4], 3, dims, strides, box)) return;
        }
    }
    p.out = (__nv_bfloat16*)d_out;
    fused_decode_kernel<<<128, NTHREADS, SMEM_BYTES>>>(p);
}
```

```cpp
#include <cuda_runtime.h>
#include <cuda_bf16.h>
#include <cuda.h>
#include <stdint.h>
#include <stdio.h>

namespace {

constexpr int DM = 640;
constexpr int NH = 32;
constexpr int SK = 8192;
constexpr int DH = 192;

constexpr int NSLOT      = 8;
constexpr int SLOT_BYTES = 24576;
constexpr int N_WQ   = 5;
constexpr int N_PAIR = SK / 64;
constexpr int N_WO   = 6;
constexpr int T_KV0  = N_WQ;
constexpr int T_WO0  = N_WQ + 2 * N_PAIR;
constexpr int N_TILES = T_WO0 + N_WO;
constexpr int WO_BYTES = 32 * 640;

constexpr int NTHREADS = 320;

constexpr int QP_STRIDE_B = 208;
constexpr int OB_STRIDE = 112;
constexpr int OFF_RING  = 0;
constexpr int OFF_PART  = NSLOT * SLOT_BYTES;
constexpr int OFF_QOWN  = OFF_PART + 8 * 2 * QP_STRIDE_B * 4;
constexpr int OFF_QPEER = OFF_QOWN + DH * 4;
constexpr int OFF_OBUF  = OFF_QPEER + DH * 4;
constexpr int OFF_ML    = OFF_OBUF + 2 * OB_STRIDE * 4;
constexpr int OFF_BARS  = OFF_ML + 8 * 2 * 4;
constexpr int OFF_EPOCH = OFF_BARS + (2 * NSLOT + 2 + N_WO) * 8;
constexpr int OFF_PROG  = OFF_EPOCH + 4;
constexpr int OFF_DEPTH = OFF_EPOCH + 8;
constexpr int OFF_GO    = OFF_EPOCH + 12;
constexpr int SMEM_USED = OFF_EPOCH + 16;
constexpr int SMEM_BYTES = SMEM_USED + 1024;

struct alignas(64) Params {
    CUtensorMap k[2];
    CUtensorMap v[2];
    CUtensorMap wq[2];
    CUtensorMap wo[2];
    const __nv_bfloat16* x[2];
    __nv_bfloat16* out;
};

__device__ unsigned long long g_part[2 * 2 * NH * 640];
__device__ unsigned int g_prog;
__device__ unsigned int g_epoch[4];
__device__ unsigned int g_done[4];

#define PACE 1
#define PACE_E 2
#define PACE_STOP 254
#define PACE_REL 0
#define PACE_WO 1
#define PACE_SLEEP 0
#define WO_GATE 2
#define PACE_D0 7
#define PACE_SL 4
#define PACE_OFS (1 - PACE_E / 2)
#define PACE_DMIN 2
#define NLATE_V 4
constexpr unsigned SPIN_LIMIT = 1u << 24;

#define TS(i) do { } while (0)

__device__ __forceinline__ uint32_t smem_u32(const void* p) { return (uint32_t)__cvta_generic_to_shared(p); }

__device__ __forceinline__ void mbar_init(uint32_t bar, uint32_t cnt) {
    asm volatile("mbarrier.init.shared::cta.b64 [%0], %1;" ::"r"(bar), "r"(cnt) : "memory");
}
__device__ __forceinline__ void mbar_expect_tx(uint32_t bar, uint32_t bytes) {
    asm volatile("mbarrier.arrive.expect_tx.shared::cta.b64 _, [%0], %1;" ::"r"(bar), "r"(bytes) : "memory");
}
__device__ __forceinline__ void mbar_arrive(uint32_t bar) {
    asm volatile("mbarrier.arrive.shared::cta.b64 _, [%0];" ::"r"(bar) : "memory");
}
__device__ __forceinline__ bool mbar_try(uint32_t bar, uint32_t parity) {
    uint32_t ok;
    asm volatile("{\n.reg .pred p;\nmbarrier.try_wait.parity.shared::cta.b64 p, [%1], %2;\nselp.u32 %0, 1, 0, p;\n}"
                 : "=r"(ok) : "r"(bar), "r"(parity) : "memory");
    return ok != 0;
}
__device__ __forceinline__ bool mbar_test(uint32_t bar, uint32_t parity) {
    uint32_t ok;
    asm volatile("{\n.reg .pred p;\nmbarrier.test_wait.parity.shared::cta.b64 p, [%1], %2;\nselp.u32 %0, 1, 0, p;\n}"
                 : "=r"(ok) : "r"(bar), "r"(parity) : "memory");
    return ok != 0;
}
__device__ __forceinline__ bool mbar_try_cluster(uint32_t bar, uint32_t parity) {
    uint32_t ok;
    asm volatile("{\n.reg .pred p;\nmbarrier.try_wait.parity.acquire.cluster.shared::cta.b64 p, [%1], %2;\nselp.u32 %0, 1, 0, p;\n}"
                 : "=r"(ok) : "r"(bar), "r"(parity) : "memory");
    return ok != 0;
}
__device__ __forceinline__ void mbar_wait(uint32_t bar, uint32_t parity) {
    unsigned n = 0;
    while (!mbar_try(bar, parity)) { if (++n > SPIN_LIMIT) __trap(); }
}
__device__ __forceinline__ void mbar_wait_cluster(uint32_t bar, uint32_t parity) {
    unsigned n = 0;
    while (!mbar_try_cluster(bar, parity)) { if (++n > SPIN_LIMIT) __trap(); }
}
__device__ __forceinline__ void tma2d(uint32_t dst, const CUtensorMap* tm, int c0, int c1, uint32_t bar, uint64_t pol) {
    asm volatile("cp.async.bulk.tensor.2d.shared::cluster.global.mbarrier::complete_tx::bytes.L2::cache_hint"
                 " [%0], [%1, {%3, %4}], [%2], %5;"
                 ::"r"(dst), "l"(tm), "r"(bar), "r"(c0), "r"(c1), "l"(pol) : "memory");
}
__device__ __forceinline__ void tma3d(uint32_t dst, const CUtensorMap* tm, int c0, int c1, int c2, uint32_t bar, uint64_t pol) {
    asm volatile("cp.async.bulk.tensor.3d.shared::cluster.global.mbarrier::complete_tx::bytes.L2::cache_hint"
                 " [%0], [%1, {%3, %4, %5}], [%2], %6;"
                 ::"r"(dst), "l"(tm), "r"(bar), "r"(c0), "r"(c1), "r"(c2), "l"(pol) : "memory");
}
__device__ __forceinline__ void ldsm4(uint32_t (&a)[4], uint32_t addr) {
    asm volatile("ldmatrix.sync.aligned.m8n8.x4.shared.b16 {%0,%1,%2,%3}, [%4];"
                 : "=r"(a[0]), "=r"(a[1]), "=r"(a[2]), "=r"(a[3]) : "r"(addr) : "memory");
}
__device__ __forceinline__ void ldsm4t(uint32_t (&a)[4], uint32_t addr) {
    asm volatile("ldmatrix.sync.aligned.m8n8.x4.trans.shared.b16 {%0,%1,%2,%3}, [%4];"
                 : "=r"(a[0]), "=r"(a[1]), "=r"(a[2]), "=r"(a[3]) : "r"(addr) : "memory");
}
__device__ __forceinline__ void mma16816(float (&c)[4], const uint32_t (&a)[4], uint32_t b0, uint32_t b1) {
    asm volatile("mma.sync.aligned.m16n8k16.row.col.f32.bf16.bf16.f32 {%0,%1,%2,%3}, {%4,%5,%6,%7}, {%8,%9}, {%0,%1,%2,%3};"
                 : "+f"(c[0]), "+f"(c[1]), "+f"(c[2]), "+f"(c[3])
                 : "r"(a[0]), "r"(a[1]), "r"(a[2]), "r"(a[3]), "r"(b0), "r"(b1));
}
__device__ __forceinline__ float ex2(float x) {
    float y;
    asm("ex2.approx.ftz.f32 %0, %1;" : "=f"(y) : "f"(x));
    return y;
}
__device__ __forceinline__ float rcp(float x) {
    float y;
    asm("rcp.approx.ftz.f32 %0, %1;" : "=f"(y) : "f"(x));
    return y;
}
__device__ __forceinline__ uint32_t pack_bf16(float lo, float hi) {
    uint32_t r;
    asm("cvt.rn.bf16x2.f32 %0, %1, %2;" : "=r"(r) : "f"(hi), "f"(lo));
    return r;
}
__device__ __forceinline__ uint32_t mapa(uint32_t addr, uint32_t cta) {
    uint32_t r;
    asm("mapa.shared::cluster.u32 %0, %1, %2;" : "=r"(r) : "r"(addr), "r"(cta));
    return r;
}
__device__ __forceinline__ void st_async_b32(uint32_t raddr, uint32_t v, uint32_t rbar) {
    asm volatile("st.async.weak.shared::cluster.mbarrier::complete_tx::bytes.b32 [%0], %1, [%2];"
                 ::"r"(raddr), "r"(v), "r"(rbar) : "memory");
}
__device__ __forceinline__ void cons_sync() { asm volatile("bar.sync 1, 256;" ::: "memory"); }
__device__ __forceinline__ void part_arrive() { asm volatile("bar.arrive 2, 288;" ::: "memory"); }
__device__ __forceinline__ void part_sync() { asm volatile("bar.sync 2, 288;" ::: "memory"); }
__device__ __forceinline__ float sel4(int t, float a, float b, float c, float d) {
    const float lo = (t & 1) ? b : a, hi = (t & 1) ? d : c;
    return (t & 2) ? hi : lo;
}
__device__ __forceinline__ void cluster_arrive() { asm volatile("barrier.cluster.arrive.relaxed.aligned;" ::: "memory"); }
__device__ __forceinline__ void cluster_wait() { asm volatile("barrier.cluster.wait.acquire.aligned;" ::: "memory"); }

__device__ __forceinline__ void pv_step(float (&acc)[12][4], uint32_t tile_addr, const uint32_t (&voff)[3],
                                        uint32_t b0, uint32_t b1) {
#pragma unroll
    for (int mt = 0; mt < 12; ++mt) {
        uint32_t a[4];
        ldsm4t(a, (tile_addr + voff[mt >> 2]) ^ ((mt & 3) << 5));
        mma16816(acc[mt], a, b0, b1);
    }
}

__global__ void __cluster_dims__(2, 1, 1) __launch_bounds__(NTHREADS, 1)
fused_decode_kernel(const __grid_constant__ Params p) {
    extern __shared__ uint8_t smem_raw[];
    const uint32_t sbase = (smem_u32(smem_raw) + 1023u) & ~1023u;
    uint8_t* sgen = smem_raw + (sbase - smem_u32(smem_raw));

    const int tid  = threadIdx.x;
    const int warp = tid >> 5;
    const int lane = tid & 31;
    const int r    = blockIdx.x & 1;
    const int cl   = blockIdx.x >> 1;
    const int br   = cl >> 5;
    const int h    = cl & 31;

    const uint32_t ring  = sbase + OFF_RING;
    const uint32_t fullb = sbase + OFF_BARS;
    const uint32_t emptb = fullb + NSLOT * 8;
    const uint32_t xqb   = emptb + NSLOT * 8;
    const uint32_t xob   = xqb + 8;
    const uint32_t wob   = xob + 8;

    if (warp == 8) {
        uint64_t pol = 0;
        const int kv_line0 = (r * NH + h) * SK * 3;
        auto issue = [&](int i) {
            const int s = i & (NSLOT - 1);
            const uint32_t dst = ring + s * SLOT_BYTES;
            const uint32_t bar = fullb + s * 8;
            if (i < T_KV0) {
                mbar_expect_tx(bar, SLOT_BYTES);
                tma3d(dst, &p.wq[br], 0, 3 * h, 320 * r + 64 * i, bar, pol);
            } else if (i < T_WO0) {
                const int j = i - T_KV0;
                mbar_expect_tx(bar, SLOT_BYTES);
                tma2d(dst, (j & 1) ? &p.v[br] : &p.k[br], 0, kv_line0 + (j >> 1) * 192, bar, pol);
            } else {
                const uint32_t wb = wob + (i - T_WO0) * 8;
                mbar_expect_tx(wb, WO_BYTES);
                tma3d(dst, &p.wo[br], 0, 5 * r, DH * h + 32 * (i - T_WO0), wb, pol);
            }
        };
        if (lane == 0) {
            TS(0);
            for (int s = 0; s < NSLOT; ++s) { mbar_init(fullb + s * 8, 1); mbar_init(emptb + s * 8, 4); }
            *reinterpret_cast<volatile unsigned*>(sgen + OFF_PROG) = 0;
            *reinterpret_cast<volatile int*>(sgen + OFF_DEPTH) = NSLOT;
            *reinterpret_cast<volatile unsigned*>(sgen + OFF_GO) = 0;
            mbar_init(xqb, 1);
            mbar_init(xob, 2);
            for (int k = 0; k < N_WO; ++k) mbar_init(wob + k * 8, 1);
            asm volatile("fence.mbarrier_init.release.cluster;" ::: "memory");
            asm volatile("createpolicy.fractional.L2::evict_first.b64 %0, 1.0;" : "=l"(pol));
            for (int i = 0; i < NSLOT; ++i) issue(i);
            mbar_expect_tx(xqb, DH * 4);
            mbar_expect_tx(xob, DH * 2);
        }
        __syncwarp();
        asm volatile("bar.arrive 4, 64;" ::: "memory");
        cluster_arrive();
        cluster_wait();
        if (lane == 0) {
            volatile unsigned* prog = reinterpret_cast<volatile unsigned*>(sgen + OFF_PROG);
            volatile int* depth = reinterpret_cast<volatile int*>(sgen + OFF_DEPTH);
            for (int i = NSLOT; i < N_TILES; ++i) {
                mbar_wait(emptb + (i & (NSLOT - 1)) * 8, ((i >> 3) & 1) ^ 1);
                *prog = i - NSLOT + 1;
                if (i < T_WO0) {
                    unsigned n = 0;
                    while (true) {
                        const int D = *depth;
                        if (D >= NSLOT) break;
                        const int x = i - D;
                        if (mbar_test(emptb + (x & (NSLOT - 1)) * 8, (x >> 3) & 1)) break;
                        if (++n > SPIN_LIMIT) __trap();
                    }
                }
                if (i == T_WO0) {
                    unsigned n = 0;
                    while (*reinterpret_cast<volatile unsigned*>(sgen + OFF_GO) == 0) { if (++n > SPIN_LIMIT) __trap(); }
                }
                issue(i);
            }
        }
        __syncwarp();
        {
            const float* part = reinterpret_cast<const float*>(sgen + OFF_PART);
            const float* ml   = reinterpret_cast<const float*>(sgen + OFF_ML);
            uint32_t* obuf    = reinterpret_cast<uint32_t*>(sgen + OFF_OBUF);
            const float sc = 0.07216878364870322f * 1.4426950408889634f;
            const int u = lane & 7;
            const int pos0 = r * OB_STRIDE + 16 * (lane >> 4) + 4 * (u & 3) + 2 * ((lane >> 3) & 1) + (u >> 2);
            const uint32_t ra = mapa(sbase + OFF_OBUF + pos0 * 4, r ^ 1), rb = mapa(xob, r ^ 1);
            part_sync();
            const float4 ml0 = *reinterpret_cast<const float4*>(ml), ml1 = *reinterpret_cast<const float4*>(ml + 4);
            const float4 ml2 = *reinterpret_cast<const float4*>(ml + 8), ml3 = *reinterpret_cast<const float4*>(ml + 12);
            float2 pv[8][3];
#pragma unroll
            for (int w = 0; w < 8; ++w)
#pragma unroll
                for (int k = 0; k < 3; ++k) pv[w][k] = *reinterpret_cast<const float2*>(part + w * DH + 2 * (lane + 32 * k));
            const float mw[8] = {ml0.x, ml0.z, ml1.x, ml1.z, ml2.x, ml2.z, ml3.x, ml3.z};
            const float lw[8] = {ml0.y, ml0.w, ml1.y, ml1.w, ml2.y, ml2.w, ml3.y, ml3.w};
            const float M = fmaxf(fmaxf(fmaxf(mw[0], mw[1]), fmaxf(mw[2], mw[3])), fmaxf(fmaxf(mw[4], mw[5]), fmaxf(mw[6], mw[7])));
            float L = 0.f, o[3][2] = {{0.f, 0.f}, {0.f, 0.f}, {0.f, 0.f}};
#pragma unroll
            for (int w = 0; w < 8; ++w) {
                const float f = ex2((mw[w] - M) * sc);
                L = fmaf(f, lw[w], L);
#pragma unroll
                for (int k = 0; k < 3; ++k) {
                    o[k][0] = fmaf(f, pv[w][k].x, o[k][0]);
                    o[k][1] = fmaf(f, pv[w][k].y, o[k][1]);
                }
            }
            const float inv = rcp(L);
#pragma unroll
            for (int k = 0; k < 3; ++k) {
                const uint32_t ob = pack_bf16(o[k][0] * inv, o[k][1] * inv);
                obuf[pos0 + 32 * k] = ob;
                st_async_b32(ra + 128 * k, ob, rb);
            }
            __syncwarp();
            if (lane == 0) { mbar_arrive(xob); TS(5); }
        }
    } else if (warp == 9) {
        cluster_arrive();
        cluster_wait();
        asm volatile("bar.sync 4, 64;" ::: "memory");
        if (lane == 0) {
            constexpr unsigned ADDS = PACE_STOP;
            volatile unsigned* prog = reinterpret_cast<volatile unsigned*>(sgen + OFF_PROG);
            volatile int* depth = reinterpret_cast<volatile int*>(sgen + OFF_DEPTH);
            const unsigned base = *reinterpret_cast<volatile unsigned*>(&g_epoch[br * 2 + r]) * (128u * ADDS);
            unsigned reported = 0, n = 0;
            while (reported < ADDS) {
                unsigned cur = *prog;
                cur = cur < ADDS ? cur : ADDS;
                const unsigned delta = cur - reported;
                unsigned gsum;
                if (delta) {
                    asm volatile("atom.relaxed.gpu.global.add.u32 %0, [%1], %2;" : "=r"(gsum) : "l"(&g_prog), "r"(delta) : "memory");
                    gsum += delta;
                } else {
                    asm volatile("ld.relaxed.gpu.global.u32 %0, [%1];" : "=r"(gsum) : "l"(&g_prog) : "memory");
                }
                reported = cur;
                const int lead = (int)(reported * 128u) - (int)(gsum - base);
                int D = PACE_D0 - ((PACE_SL * lead + 64) >> 7);
                *depth = D < PACE_DMIN ? PACE_DMIN : D;
                if (PACE_SLEEP) __nanosleep(PACE_SLEEP);
                if (++n > SPIN_LIMIT) __trap();
            }
            while (true) {
                unsigned gsum;
                asm volatile("ld.relaxed.gpu.global.u32 %0, [%1];" : "=r"(gsum) : "l"(&g_prog) : "memory");
                if ((int)(gsum - base) >= (int)((ADDS - WO_GATE) * 128u)) break;
                if (++n > SPIN_LIMIT) __trap();
            }
            *reinterpret_cast<volatile unsigned*>(sgen + OFF_GO) = 1;
        }
    } else {
        const int g  = lane >> 2;
        const int t  = lane & 3;
        const int gs = warp >> 2;
        const int wi = warp & 3;
        const int grp = br * 2 + r;

        uint32_t xb[3][2];
        {
            const uint32_t* xw = reinterpret_cast<const uint32_t*>(p.x[br] + (g & 1) * DM + 320 * r + 16 * wi + 2 * t);
#pragma unroll
            for (int ii = 0; ii < 3; ++ii) {
                const int i = gs + 2 * ii;
                if (i < N_WQ) { xb[ii][0] = __ldg(xw + 32 * i); xb[ii][1] = __ldg(xw + 32 * i + 4); }
                else { xb[ii][0] = 0; xb[ii][1] = 0; }
            }
        }
        unsigned epoch = 0;
        if (tid == 0) epoch = *reinterpret_cast<volatile unsigned*>(&g_epoch[grp]);

        uint32_t koff[3], voff[3];
        {
            const int rowk = 16 * wi + (lane & 7) + 8 * ((lane >> 3) & 1), hik = lane >> 4;
            const int rowv = 16 * wi + (lane & 7) + 8 * (lane >> 4),       hiv = (lane >> 3) & 1;
#pragma unroll
            for (int sg = 0; sg < 3; ++sg) {
                const int lk = 3 * rowk + sg, lv = 3 * rowv + sg;
                koff[sg] = lk * 128 + ((hik ^ (lk & 7)) << 4);
                voff[sg] = lv * 128 + ((hiv ^ (lv & 7)) << 4);
            }
        }

        cluster_arrive();
        cluster_wait();

        float acc[12][4];
#pragma unroll
        for (int mt = 0; mt < 12; ++mt) { acc[mt][0] = acc[mt][1] = acc[mt][2] = acc[mt][3] = 0.f; }

#pragma unroll
        for (int ii = 0; ii < 3; ++ii) {
            const int i = gs + 2 * ii;
            if (i < N_WQ) {
                mbar_wait(fullb + i * 8, 0);
                if (lane == 0 && wi == 0 && (i == 0 || i == 4)) TS(i == 0 ? 1 : 2);
                pv_step(acc, ring + i * SLOT_BYTES, voff, xb[ii][0], xb[ii][1]);
                __syncwarp();
                if (lane == 0) mbar_arrive(emptb + i * 8);
            }
        }
        float* part = reinterpret_cast<float*>(sgen + OFF_PART);
        float* qown = reinterpret_cast<float*>(sgen + OFF_QOWN);
        float* qpeer = reinterpret_cast<float*>(sgen + OFF_QPEER);
        {
            float* dst = part + (warp * 2 + (t & 1)) * QP_STRIDE_B + g + 8 * (t >> 1);
#pragma unroll
            for (int mt = 0; mt < 12; ++mt) {
                const float v = sel4(t, acc[mt][0], acc[mt][1], acc[mt][2], acc[mt][3]);
                dst[16 * mt] = v;
            }
            if (tid == 0) *reinterpret_cast<unsigned*>(sgen + OFF_EPOCH) = epoch;
        }
        cons_sync();
        if (tid < DH) {
            float own = 0.f, oth = 0.f;
#pragma unroll
            for (int w = 0; w < 8; ++w) {
                own += part[(w * 2 + r) * QP_STRIDE_B + tid];
                oth += part[(w * 2 + (r ^ 1)) * QP_STRIDE_B + tid];
            }
            qown[tid] = own;
            st_async_b32(mapa(sbase + OFF_QPEER + tid * 4, r ^ 1), __float_as_uint(oth), mapa(xqb, r ^ 1));
        }
        cons_sync();
        mbar_wait_cluster(xqb, 0);
        epoch = *reinterpret_cast<volatile unsigned*>(sgen + OFF_EPOCH);

        uint32_t qb[12][2];
#pragma unroll
        for (int s = 0; s < 12; ++s) {
            const int c = 16 * s + 2 * t;
            qb[s][0] = pack_bf16(qown[c] + qpeer[c], qown[c + 1] + qpeer[c + 1]);
            qb[s][1] = pack_bf16(qown[c + 8] + qpeer[c + 8], qown[c + 9] + qpeer[c + 9]);
        }

        auto pub_addr = [&](int q) {
            const int o = (t & 1) * 320 + 16 * (warp + 8 * q) + g + 8 * (t >> 1);
            const int red = (o * 3277) >> 16;
            return g_part + ((size_t)(grp * NH + red) * NH + h) * 20 + (o - 20 * red);
        };
        auto prewrite = [&]() {
#pragma unroll
            for (int q = 0; q < 3; ++q)
                if (q < 2 || warp < 4)
                    asm volatile("st.relaxed.gpu.global.b64 [%0], %1;" ::"l"(pub_addr(q)), "l"((unsigned long long)epoch << 32) : "memory");
        };
        prewrite();
        if (tid == 0) TS(3);
#pragma unroll
        for (int mt = 0; mt < 12; ++mt) { acc[mt][0] = acc[mt][1] = acc[mt][2] = acc[mt][3] = 0.f; }
        const float sc = 0.07216878364870322f * 1.4426950408889634f;
        float m = -INFINITY, l = 0.f;

#pragma unroll 1
        for (int jj = 0; jj < N_PAIR / 2; ++jj) {
            const int iK = T_KV0 + 2 * (2 * jj + gs);
            const int iV = iK + 1;
            const int sK = iK & (NSLOT - 1), sV = iV & (NSLOT - 1);

            mbar_wait(fullb + sK * 8, (iK >> 3) & 1);
            float cA[4] = {0.f, 0.f, 0.f, 0.f}, cB[4] = {0.f, 0.f, 0.f, 0.f};
            {
                const uint32_t kt = ring + sK * SLOT_BYTES;
#pragma unroll
                for (int s = 0; s < 12; s += 2) {
                    uint32_t a0[4], a1[4];
                    ldsm4(a0, (kt + koff[s >> 2]) ^ ((s & 3) << 5));
                    ldsm4(a1, (kt + koff[(s + 1) >> 2]) ^ (((s + 1) & 3) << 5));
                    mma16816(cA, a0, qb[s][0], qb[s][1]);
                    mma16816(cB, a1, qb[s + 1][0], qb[s + 1][1]);
                }
            }
            __syncwarp();
            if (lane == 0) mbar_arrive(emptb + sK * 8);

            const float s0 = cA[0] + cB[0];
            const float s1 = cA[2] + cB[2];
            float bm = fmaxf(s0, s1);
            bm = fmaxf(bm, __shfl_xor_sync(0xffffffffu, bm, 4));
            bm = fmaxf(bm, __shfl_xor_sync(0xffffffffu, bm, 8));
            bm = fmaxf(bm, __shfl_xor_sync(0xffffffffu, bm, 16));
            if (bm > m) {
                const float f = ex2((m - bm) * sc);
                l *= f;
#pragma unroll
                for (int mt = 0; mt < 12; ++mt) { acc[mt][0] *= f; acc[mt][2] *= f; }
                m = bm;
            }
            const float ms = m * sc;
            const float p0 = ex2(fmaf(s0, sc, -ms));
            const float p1 = ex2(fmaf(s1, sc, -ms));
            l += p0 + p1;
            const uint32_t pk = pack_bf16(p0, p1);
            const uint32_t u = __shfl_sync(0xffffffffu, pk, 8 * t);
            const uint32_t v = __shfl_sync(0xffffffffu, pk, 8 * t + 4);
            const uint32_t b0 = __byte_perm(u, v, 0x5410);
            const uint32_t b1 = __byte_perm(u, v, 0x7632);

            mbar_wait(fullb + sV * 8, (iV >> 3) & 1);
            pv_step(acc, ring + sV * SLOT_BYTES, voff, b0, b1);
            __syncwarp();
            if (lane == 0) mbar_arrive(emptb + sV * 8);
        }

        if (tid == 128) {
            TS(4);
            asm volatile("red.relaxed.gpu.global.add.u32 [%0], 1;" ::"l"(&g_done[grp]) : "memory");
        }
        l += __shfl_xor_sync(0xffffffffu, l, 4);
        l += __shfl_xor_sync(0xffffffffu, l, 8);
        l += __shfl_xor_sync(0xffffffffu, l, 16);
        float* ml = reinterpret_cast<float*>(sgen + OFF_ML);
        if (t < 2) {
            float* dst = part + warp * DH + g + 8 * t;
#pragma unroll
            for (int mt = 0; mt < 12; ++mt) dst[16 * mt] = t ? acc[mt][2] : acc[mt][0];
        }
        if (lane == 0) { ml[warp * 2] = m; ml[warp * 2 + 1] = l; }
        part_arrive();

        unsigned long long* pub[3];
#pragma unroll
        for (int q = 0; q < 3; ++q) {
            pub[q] = pub_addr(q);
            asm volatile("" : "+l"(pub[q]));
        }
        const unsigned long long* src = g_part + (size_t)(grp * NH + h) * 640 + tid;
        const int oj = 20 * h + (tid >> 3);
        __nv_bfloat16* dsto = p.out + (oj >= 320 ? 2 * DM - 320 : 0) + br * DM + r * 320 + oj;
        const unsigned int* donep = &g_done[grp];
        asm volatile("" : "+l"(src), "+l"(dsto), "+l"(donep));

        uint32_t woff[3][2];
        {
            const int rowt = (lane & 7) + 8 * (lane >> 4), hit = (lane >> 3) & 1;
#pragma unroll
            for (int q = 0; q < 3; ++q) {
                const int mt = warp + 8 * q;
#pragma unroll
                for (int kk = 0; kk < 2; ++kk) {
                    const int line = 5 * (16 * kk + rowt) + (mt >> 2);
                    woff[q][kk] = ring + line * 128 + (((2 * (mt & 3) + hit) ^ (line & 7)) << 4);
                }
            }
        }
        constexpr int NLATE = NLATE_V;
        uint32_t wa[2][12][4];
        bool late[NLATE];
#pragma unroll
        for (int i = 0; i < N_WO; ++i) {
            const uint32_t so = ((T_WO0 + i) & (NSLOT - 1)) * SLOT_BYTES;
            bool in = true;
            if (i < N_WO - NLATE) mbar_wait(wob + i * 8, 0);
            else { in = __all_sync(0xffffffffu, mbar_test(wob + i * 8, 0)); late[i - (N_WO - NLATE)] = !in; }
            if (in) {
#pragma unroll
                for (int q = 0; q < 2; ++q) {
                    ldsm4t(wa[q][2 * i], woff[q][0] + so);
                    ldsm4t(wa[q][2 * i + 1], woff[q][1] + so);
                }
            }
        }
        mbar_wait_cluster(xob, 0);
        if (tid == 0) TS(6);

        float oc[3][2][4];
#pragma unroll
        for (int q = 0; q < 3; ++q)
#pragma unroll
            for (int kk = 0; kk < 2; ++kk) { oc[q][kk][0] = oc[q][kk][1] = oc[q][kk][2] = oc[q][kk][3] = 0.f; }
        {
            const uint32_t* obuf = reinterpret_cast<const uint32_t*>(sgen + OFF_OBUF);
            const uint4* os = reinterpret_cast<const uint4*>(obuf + (g & 1) * OB_STRIDE + 4 * t);
            uint4 b[N_WO];
#pragma unroll
            for (int i = 0; i < N_WO; ++i) b[i] = os[4 * i];
#pragma unroll
            for (int i = 0; i < N_WO; ++i) {
                const uint32_t so = ((T_WO0 + i) & (NSLOT - 1)) * SLOT_BYTES;
                if (i >= N_WO - NLATE && late[i - (N_WO - NLATE)]) {
                    mbar_wait(wob + i * 8, 0);
#pragma unroll
                    for (int q = 0; q < 2; ++q) {
                        ldsm4t(wa[q][2 * i], woff[q][0] + so);
                        ldsm4t(wa[q][2 * i + 1], woff[q][1] + so);
                    }
                }
                uint32_t wb[2][4];
                if (warp < 4) { ldsm4t(wb[0], woff[2][0] + so); ldsm4t(wb[1], woff[2][1] + so); }
#pragma unroll
                for (int q = 0; q < 2; ++q) {
                    mma16816(oc[q][0], wa[q][2 * i], b[i].x, b[i].y);
                    mma16816(oc[q][1], wa[q][2 * i + 1], b[i].z, b[i].w);
                }
                if (warp < 4) {
                    mma16816(oc[2][0], wb[0], b[i].x, b[i].y);
                    mma16816(oc[2][1], wb[1], b[i].z, b[i].w);
                }
            }
        }
        if (tid == 0) TS(7);
        const unsigned tag = epoch + 1u;
#pragma unroll
        for (int q = 0; q < 3; ++q) {
            const float v = sel4(t, oc[q][0][0] + oc[q][1][0], oc[q][0][1] + oc[q][1][1],
                                    oc[q][0][2] + oc[q][1][2], oc[q][0][3] + oc[q][1][3]);
            const unsigned long long w = ((unsigned long long)tag << 32) | __float_as_uint(v);
            if (q < 2 || warp < 4)
                asm volatile("st.relaxed.gpu.global.b64 [%0], %1;" ::"l"(pub[q]), "l"(w) : "memory");
        }
        if (tid == 0) TS(9);
        if (tid < 160) {
            float v[4] = {0.f, 0.f, 0.f, 0.f};
            {
                unsigned n = 0, c;
                bool have[4] = {false, false, false, false};
                asm volatile("ld.relaxed.gpu.global.u32 %0, [%1];" : "=r"(c) : "l"(donep) : "memory");
                while (true) {
                    unsigned long long w[4] = {0ull, 0ull, 0ull, 0ull};
#pragma unroll
                    for (int i = 0; i < 4; ++i)
                        if (!have[i]) asm volatile("ld.relaxed.gpu.global.b64 %0, [%1];" : "=l"(w[i]) : "l"(src + i * 160) : "memory");
#pragma unroll
                    for (int i = 0; i < 4; ++i)
                        if (!have[i] && (unsigned)(w[i] >> 32) == tag) { have[i] = true; v[i] = __uint_as_float((unsigned)w[i]); }
                    if (__all_sync(0xffffffffu, have[0] && have[1] && have[2] && have[3])) break;
                    while ((int)(c - tag * NH) < 0) {
                        __nanosleep(300);
                        asm volatile("ld.relaxed.gpu.global.u32 %0, [%1];" : "=r"(c) : "l"(donep) : "memory");
                        if (++n > SPIN_LIMIT) __trap();
                    }
                    if (++n > SPIN_LIMIT) __trap();
                }
            }
            float* red = reinterpret_cast<float*>(sgen + OFF_PART);
#pragma unroll
            for (int i = 0; i < 4; ++i) red[tid + 160 * i] = v[i];
            asm volatile("bar.sync 3, 160;" ::: "memory");
            const int j = tid >> 3, s = tid & 7;
#pragma unroll
            for (int i = 0; i < 4; ++i) v[i] = red[(4 * s + i) * 20 + j];
            float sum = (v[0] + v[1]) + (v[2] + v[3]);
            sum += __shfl_xor_sync(0xffffffffu, sum, 1);
            sum += __shfl_xor_sync(0xffffffffu, sum, 2);
            sum += __shfl_xor_sync(0xffffffffu, sum, 4);
            if (s == 0) *dsto = __float2bfloat16(sum);
            if (tid == 0) { TS(8);
            }
            if (h == 0 && tid == 0) *reinterpret_cast<volatile unsigned*>(&g_epoch[grp]) = tag;
        }
    }
}

typedef CUresult (*EncodeTiledFn)(CUtensorMap*, CUtensorMapDataType, cuuint32_t, void*, const cuuint64_t*,
                                  const cuuint64_t*, const cuuint32_t*, const cuuint32_t*, CUtensorMapInterleave,
                                  CUtensorMapSwizzle, CUtensorMapL2promotion, CUtensorMapFloatOOBfill);

bool encode(EncodeTiledFn fn, CUtensorMap* tm, const void* ptr, int rank, const cuuint64_t* dims,
            const cuuint64_t* strides, const cuuint32_t* box) {
    const cuuint32_t es[3] = {1, 1, 1};
    CUresult rc = fn(tm, CU_TENSOR_MAP_DATA_TYPE_BFLOAT16, (cuuint32_t)rank, const_cast<void*>(ptr), dims, strides, box, es,
                     CU_TENSOR_MAP_INTERLEAVE_NONE, CU_TENSOR_MAP_SWIZZLE_128B, CU_TENSOR_MAP_L2_PROMOTION_L2_128B,
                     CU_TENSOR_MAP_FLOAT_OOB_FILL_NONE);
    if (rc != CUDA_SUCCESS) { fprintf(stderr, "cuTensorMapEncodeTiled failed: %d\n", (int)rc); return false; }
    return true;
}

}

extern "C" void kernel_launch(void* const* d_in, const int* in_sizes, int n_in, void* d_out, int out_size) {
    (void)in_sizes; (void)n_in; (void)out_size;
    static EncodeTiledFn fn = nullptr;
    if (!fn) {
        void* f = nullptr;
        cudaDriverEntryPointQueryResult qr;
        if (cudaGetDriverEntryPoint("cuTensorMapEncodeTiled", &f, cudaEnableDefault, &qr) != cudaSuccess || !f) {
            fprintf(stderr, "cuTensorMapEncodeTiled not available\n");
            return;
        }
        fn = (EncodeTiledFn)f;
        cudaFuncSetAttribute(fused_decode_kernel, cudaFuncAttributeMaxDynamicSharedMemorySize, SMEM_BYTES);
    }
    Params p;
    for (int b = 0; b < 2; ++b) {
        void* const* in = d_in + 5 * b;
        p.x[b] = (const __nv_bfloat16*)in[0];
        {
            const cuuint64_t dims[2] = {64, (cuuint64_t)2 * NH * SK * 3};
            const cuuint64_t strides[1] = {128};
            const cuuint32_t box[2] = {64, 192};
            if (!encode(fn, &p.k[b], in[1], 2, dims, strides, box)) return;
            if (!encode(fn, &p.v[b], in[2], 2, dims, strides, box)) return;
        }
        {
            const cuuint64_t dims[3] = {64, 96, 640};
            const cuuint64_t strides[2] = {128, 12288};
            const cuuint32_t box[3] = {64, 3, 64};
            if (!encode(fn, &p.wq[b], in[3], 3, dims, strides, box)) return;
        }
        {
            const cuuint64_t dims[3] = {64, 10, 6144};
            const cuuint64_t strides[2] = {128, 1280};
            const cuuint32_t box[3] = {64, 5, 32};
            if (!encode(fn, &p.wo[b], in[4], 3, dims, strides, box)) return;
        }
    }
    p.out = (__nv_bfloat16*)d_out;
    fused_decode_kernel<<<128, NTHREADS, SMEM_BYTES>>>(p);
}
```

```cpp
#include <cuda_runtime.h>
#include <cuda_bf16.h>
#include <cuda.h>
#include <stdint.h>
#include <stdio.h>

namespace {

constexpr int DM = 640;
constexpr int NH = 32;
constexpr int SK = 8192;
constexpr int DH = 192;

constexpr int NSLOT      = 8;
constexpr int SLOT_BYTES = 24576;
constexpr int N_WQ   = 5;
constexpr int N_PAIR = SK / 64;
constexpr int N_WO   = 6;
constexpr int T_KV0  = N_WQ;
constexpr int T_WO0  = N_WQ + 2 * N_PAIR;
constexpr int N_TILES = T_WO0 + N_WO;
constexpr int WO_BYTES = 32 * 640;

constexpr int NTHREADS = 320;

constexpr int QP_STRIDE_B = 208;
constexpr int OB_STRIDE = 112;
constexpr int OFF_RING  = 0;
constexpr int OFF_PART  = NSLOT * SLOT_BYTES;
constexpr int OFF_QOWN  = OFF_PART + 8 * 2 * QP_STRIDE_B * 4;
constexpr int OFF_QPEER = OFF_QOWN + DH * 4;
constexpr int OFF_OBUF  = OFF_QPEER + DH * 4;
constexpr int OFF_ML    = OFF_OBUF + 2 * OB_STRIDE * 4;
constexpr int OFF_BARS  = OFF_ML + 8 * 2 * 4;
constexpr int OFF_EPOCH = OFF_BARS + (2 * NSLOT + 2 + N_WO) * 8;
constexpr int OFF_PROG  = OFF_EPOCH + 4;
constexpr int OFF_DEPTH = OFF_EPOCH + 8;
constexpr int OFF_GO    = OFF_EPOCH + 12;
constexpr int SMEM_USED = OFF_EPOCH + 16;
constexpr int SMEM_BYTES = SMEM_USED + 1024;

struct alignas(64) Params {
    CUtensorMap k[2];
    CUtensorMap v[2];
    CUtensorMap wq[2];
    CUtensorMap wo[2];
    const __nv_bfloat16* x[2];
    __nv_bfloat16* out;
};

__device__ unsigned long long g_part[2 * 2 * NH * 640];
__device__ unsigned int g_prog;
__device__ unsigned int g_epoch[4];
__device__ unsigned int g_done[4];

constexpr int PACE_D0 = 7, PACE_SL = 4, PACE_DMIN = 2;
constexpr unsigned PACE_TILES = T_WO0 - NSLOT + 1;
constexpr unsigned WO_GATE = 2;

constexpr unsigned SPIN_LIMIT = 1u << 24;

#define TS(i) do { } while (0)

__device__ __forceinline__ uint32_t smem_u32(const void* p) { return (uint32_t)__cvta_generic_to_shared(p); }

__device__ __forceinline__ void mbar_init(uint32_t bar, uint32_t cnt) {
    asm volatile("mbarrier.init.shared::cta.b64 [%0], %1;" ::"r"(bar), "r"(cnt) : "memory");
}
__device__ __forceinline__ void mbar_expect_tx(uint32_t bar, uint32_t bytes) {
    asm volatile("mbarrier.arrive.expect_tx.shared::cta.b64 _, [%0], %1;" ::"r"(bar), "r"(bytes) : "memory");
}
__device__ __forceinline__ void mbar_arrive(uint32_t bar) {
    asm volatile("mbarrier.arrive.shared::cta.b64 _, [%0];" ::"r"(bar) : "memory");
}
__device__ __forceinline__ bool mbar_try(uint32_t bar, uint32_t parity) {
    uint32_t ok;
    asm volatile("{\n.reg .pred p;\nmbarrier.try_wait.parity.shared::cta.b64 p, [%1], %2;\nselp.u32 %0, 1, 0, p;\n}"
                 : "=r"(ok) : "r"(bar), "r"(parity) : "memory");
    return ok != 0;
}
__device__ __forceinline__ bool mbar_test(uint32_t bar, uint32_t parity) {
    uint32_t ok;
    asm volatile("{\n.reg .pred p;\nmbarrier.test_wait.parity.shared::cta.b64 p, [%1], %2;\nselp.u32 %0, 1, 0, p;\n}"
                 : "=r"(ok) : "r"(bar), "r"(parity) : "memory");
    return ok != 0;
}
__device__ __forceinline__ bool mbar_try_cluster(uint32_t bar, uint32_t parity) {
    uint32_t ok;
    asm volatile("{\n.reg .pred p;\nmbarrier.try_wait.parity.acquire.cluster.shared::cta.b64 p, [%1], %2;\nselp.u32 %0, 1, 0, p;\n}"
                 : "=r"(ok) : "r"(bar), "r"(parity) : "memory");
    return ok != 0;
}
__device__ __forceinline__ void mbar_wait(uint32_t bar, uint32_t parity) {
    unsigned n = 0;
    while (!mbar_try(bar, parity)) { if (++n > SPIN_LIMIT) __trap(); }
}
__device__ __forceinline__ void mbar_wait_cluster(uint32_t bar, uint32_t parity) {
    unsigned n = 0;
    while (!mbar_try_cluster(bar, parity)) { if (++n > SPIN_LIMIT) __trap(); }
}
__device__ __forceinline__ void tma2d(uint32_t dst, const CUtensorMap* tm, int c0, int c1, uint32_t bar, uint64_t pol) {
    asm volatile("cp.async.bulk.tensor.2d.shared::cluster.global.mbarrier::complete_tx::bytes.L2::cache_hint"
                 " [%0], [%1, {%3, %4}], [%2], %5;"
                 ::"r"(dst), "l"(tm), "r"(bar), "r"(c0), "r"(c1), "l"(pol) : "memory");
}
__device__ __forceinline__ void tma3d(uint32_t dst, const CUtensorMap* tm, int c0, int c1, int c2, uint32_t bar, uint64_t pol) {
    asm volatile("cp.async.bulk.tensor.3d.shared::cluster.global.mbarrier::complete_tx::bytes.L2::cache_hint"
                 " [%0], [%1, {%3, %4, %5}], [%2], %6;"
                 ::"r"(dst), "l"(tm), "r"(bar), "r"(c0), "r"(c1), "r"(c2), "l"(pol) : "memory");
}
__device__ __forceinline__ void ldsm4(uint32_t (&a)[4], uint32_t addr) {
    asm volatile("ldmatrix.sync.aligned.m8n8.x4.shared.b16 {%0,%1,%2,%3}, [%4];"
                 : "=r"(a[0]), "=r"(a[1]), "=r"(a[2]), "=r"(a[3]) : "r"(addr) : "memory");
}
__device__ __forceinline__ void ldsm4t(uint32_t (&a)[4], uint32_t addr) {
    asm volatile("ldmatrix.sync.aligned.m8n8.x4.trans.shared.b16 {%0,%1,%2,%3}, [%4];"
                 : "=r"(a[0]), "=r"(a[1]), "=r"(a[2]), "=r"(a[3]) : "r"(addr) : "memory");
}
__device__ __forceinline__ void mma16816(float (&c)[4], const uint32_t (&a)[4], uint32_t b0, uint32_t b1) {
    asm volatile("mma.sync.aligned.m16n8k16.row.col.f32.bf16.bf16.f32 {%0,%1,%2,%3}, {%4,%5,%6,%7}, {%8,%9}, {%0,%1,%2,%3};"
                 : "+f"(c[0]), "+f"(c[1]), "+f"(c[2]), "+f"(c[3])
                 : "r"(a[0]), "r"(a[1]), "r"(a[2]), "r"(a[3]), "r"(b0), "r"(b1));
}
__device__ __forceinline__ float ex2(float x) {
    float y;
    asm("ex2.approx.ftz.f32 %0, %1;" : "=f"(y) : "f"(x));
    return y;
}
__device__ __forceinline__ float rcp(float x) {
    float y;
    asm("rcp.approx.ftz.f32 %0, %1;" : "=f"(y) : "f"(x));
    return y;
}
__device__ __forceinline__ uint32_t pack_bf16(float lo, float hi) {
    uint32_t r;
    asm("cvt.rn.bf16x2.f32 %0, %1, %2;" : "=r"(r) : "f"(hi), "f"(lo));
    return r;
}
__device__ __forceinline__ uint32_t mapa(uint32_t addr, uint32_t cta) {
    uint32_t r;
    asm("mapa.shared::cluster.u32 %0, %1, %2;" : "=r"(r) : "r"(addr), "r"(cta));
    return r;
}
__device__ __forceinline__ void st_async_b32(uint32_t raddr, uint32_t v, uint32_t rbar) {
    asm volatile("st.async.weak.shared::cluster.mbarrier::complete_tx::bytes.b32 [%0], %1, [%2];"
                 ::"r"(raddr), "r"(v), "r"(rbar) : "memory");
}
__device__ __forceinline__ void cons_sync() { asm volatile("bar.sync 1, 256;" ::: "memory"); }
__device__ __forceinline__ void part_arrive() { asm volatile("bar.arrive 2, 288;" ::: "memory"); }
__device__ __forceinline__ void part_sync() { asm volatile("bar.sync 2, 288;" ::: "memory"); }
__device__ __forceinline__ float sel4(int t, float a, float b, float c, float d) {
    const float lo = (t & 1) ? b : a, hi = (t & 1) ? d : c;
    return (t & 2) ? hi : lo;
}
__device__ __forceinline__ void cluster_arrive() { asm volatile("barrier.cluster.arrive.relaxed.aligned;" ::: "memory"); }
__device__ __forceinline__ void cluster_wait() { asm volatile("barrier.cluster.wait.acquire.aligned;" ::: "memory"); }

__device__ __forceinline__ void pv_step(float (&acc)[12][4], uint32_t tile_addr, const uint32_t (&voff)[3],
                                        uint32_t b0, uint32_t b1) {
#pragma unroll
    for (int mt = 0; mt < 12; ++mt) {
        uint32_t a[4];
        ldsm4t(a, (tile_addr + voff[mt >> 2]) ^ ((mt & 3) << 5));
        mma16816(acc[mt], a, b0, b1);
    }
}

__global__ void __cluster_dims__(2, 1, 1) __launch_bounds__(NTHREADS, 1)
fused_decode_kernel(const __grid_constant__ Params p) {
    extern __shared__ uint8_t smem_raw[];
    const uint32_t sbase = (smem_u32(smem_raw) + 1023u) & ~1023u;
    uint8_t* sgen = smem_raw + (sbase - smem_u32(smem_raw));

    const int tid  = threadIdx.x;
    const int warp = tid >> 5;
    const int lane = tid & 31;
    const int r    = blockIdx.x & 1;
    const int cl   = blockIdx.x >> 1;
    const int br   = cl >> 5;
    const int h    = cl & 31;

    const uint32_t ring  = sbase + OFF_RING;
    const uint32_t fullb = sbase + OFF_BARS;
    const uint32_t emptb = fullb + NSLOT * 8;
    const uint32_t xqb   = emptb + NSLOT * 8;
    const uint32_t xob   = xqb + 8;
    const uint32_t wob   = xob + 8;

    if (warp == 8) {
        uint64_t pol = 0;
        const int kv_line0 = (r * NH + h) * SK * 3;
        auto issue = [&](int i) {
            const int s = i & (NSLOT - 1);
            const uint32_t dst = ring + s * SLOT_BYTES;
            const uint32_t bar = fullb + s * 8;
            if (i < T_KV0) {
                mbar_expect_tx(bar, SLOT_BYTES);
                tma3d(dst, &p.wq[br], 0, 3 * h, 320 * r + 64 * i, bar, pol);
            } else if (i < T_WO0) {
                const int j = i - T_KV0;
                mbar_expect_tx(bar, SLOT_BYTES);
                tma2d(dst, (j & 1) ? &p.v[br] : &p.k[br], 0, kv_line0 + (j >> 1) * 192, bar, pol);
            } else {
                const uint32_t wb = wob + (i - T_WO0) * 8;
                mbar_expect_tx(wb, WO_BYTES);
                tma3d(dst, &p.wo[br], 0, 5 * r, DH * h + 32 * (i - T_WO0), wb, pol);
            }
        };
        if (lane == 0) {
            TS(0);
            for (int s = 0; s < NSLOT; ++s) { mbar_init(fullb + s * 8, 1); mbar_init(emptb + s * 8, 4); }
            *reinterpret_cast<volatile unsigned*>(sgen + OFF_PROG) = 0;
            *reinterpret_cast<volatile int*>(sgen + OFF_DEPTH) = NSLOT;
            *reinterpret_cast<volatile unsigned*>(sgen + OFF_GO) = 0;
            mbar_init(xqb, 1);
            mbar_init(xob, 2);
            for (int k = 0; k < N_WO; ++k) mbar_init(wob + k * 8, 1);
            asm volatile("fence.mbarrier_init.release.cluster;" ::: "memory");
            asm volatile("createpolicy.fractional.L2::evict_first.b64 %0, 1.0;" : "=l"(pol));
            for (int i = 0; i < NSLOT; ++i) issue(i);
            mbar_expect_tx(xqb, DH * 4);
            mbar_expect_tx(xob, DH * 2);
        }
        __syncwarp();
        asm volatile("bar.arrive 4, 64;" ::: "memory");
        cluster_arrive();
        cluster_wait();
        if (lane == 0) {
            volatile unsigned* prog = reinterpret_cast<volatile unsigned*>(sgen + OFF_PROG);
            volatile int* depth = reinterpret_cast<volatile int*>(sgen + OFF_DEPTH);
            for (int i = NSLOT; i < N_TILES; ++i) {
                mbar_wait(emptb + (i & (NSLOT - 1)) * 8, ((i >> 3) & 1) ^ 1);
                *prog = i - NSLOT + 1;
                if (i < T_WO0) {
                    unsigned n = 0;
                    while (true) {
                        const int D = *depth;
                        if (D >= NSLOT) break;
                        const int x = i - D;
                        if (mbar_test(emptb + (x & (NSLOT - 1)) * 8, (x >> 3) & 1)) break;
                        if (++n > SPIN_LIMIT) __trap();
                    }
                }
                if (i == T_WO0) {
                    unsigned n = 0;
                    while (*reinterpret_cast<volatile unsigned*>(sgen + OFF_GO) == 0) { if (++n > SPIN_LIMIT) __trap(); }
                }
                issue(i);
            }
        }
        __syncwarp();
        {
            const float* part = reinterpret_cast<const float*>(sgen + OFF_PART);
            const float* ml   = reinterpret_cast<const float*>(sgen + OFF_ML);
            uint32_t* obuf    = reinterpret_cast<uint32_t*>(sgen + OFF_OBUF);
            const float sc = 0.07216878364870322f * 1.4426950408889634f;
            const int u = lane & 7;
            const int pos0 = r * OB_STRIDE + 16 * (lane >> 4) + 4 * (u & 3) + 2 * ((lane >> 3) & 1) + (u >> 2);
            const uint32_t ra = mapa(sbase + OFF_OBUF + pos0 * 4, r ^ 1), rb = mapa(xob, r ^ 1);
            part_sync();
            const float4 ml0 = *reinterpret_cast<const float4*>(ml), ml1 = *reinterpret_cast<const float4*>(ml + 4);
            const float4 ml2 = *reinterpret_cast<const float4*>(ml + 8), ml3 = *reinterpret_cast<const float4*>(ml + 12);
            float2 pv[8][3];
#pragma unroll
            for (int w = 0; w < 8; ++w)
#pragma unroll
                for (int k = 0; k < 3; ++k) pv[w][k] = *reinterpret_cast<const float2*>(part + w * DH + 2 * (lane + 32 * k));
            const float mw[8] = {ml0.x, ml0.z, ml1.x, ml1.z, ml2.x, ml2.z, ml3.x, ml3.z};
            const float lw[8] = {ml0.y, ml0.w, ml1.y, ml1.w, ml2.y, ml2.w, ml3.y, ml3.w};
            const float M = fmaxf(fmaxf(fmaxf(mw[0], mw[1]), fmaxf(mw[2], mw[3])), fmaxf(fmaxf(mw[4], mw[5]), fmaxf(mw[6], mw[7])));
            float L = 0.f, o[3][2] = {{0.f, 0.f}, {0.f, 0.f}, {0.f, 0.f}};
#pragma unroll
            for (int w = 0; w < 8; ++w) {
                const float f = ex2((mw[w] - M) * sc);
                L = fmaf(f, lw[w], L);
#pragma unroll
                for (int k = 0; k < 3; ++k) {
                    o[k][0] = fmaf(f, pv[w][k].x, o[k][0]);
                    o[k][1] = fmaf(f, pv[w][k].y, o[k][1]);
                }
            }
            const float inv = rcp(L);
#pragma unroll
            for (int k = 0; k < 3; ++k) {
                const uint32_t ob = pack_bf16(o[k][0] * inv, o[k][1] * inv);
                obuf[pos0 + 32 * k] = ob;
                st_async_b32(ra + 128 * k, ob, rb);
            }
            __syncwarp();
            if (lane == 0) { mbar_arrive(xob); TS(5); }
        }
    } else if (warp == 9) {
        cluster_arrive();
        cluster_wait();
        asm volatile("bar.sync 4, 64;" ::: "memory");
        if (lane == 0) {
            constexpr unsigned ADDS = PACE_TILES;
            volatile unsigned* prog = reinterpret_cast<volatile unsigned*>(sgen + OFF_PROG);
            volatile int* depth = reinterpret_cast<volatile int*>(sgen + OFF_DEPTH);
            const unsigned base = *reinterpret_cast<volatile unsigned*>(&g_epoch[br * 2 + r]) * (128u * ADDS);
            unsigned reported = 0, n = 0;
            bool go = false;
            while (reported < ADDS) {
                unsigned cur = *prog;
                cur = cur < ADDS ? cur : ADDS;
                const unsigned delta = cur - reported;
                unsigned gsum;
                if (delta) {
                    asm volatile("atom.relaxed.gpu.global.add.u32 %0, [%1], %2;" : "=r"(gsum) : "l"(&g_prog), "r"(delta) : "memory");
                    gsum += delta;
                } else {
                    asm volatile("ld.relaxed.gpu.global.u32 %0, [%1];" : "=r"(gsum) : "l"(&g_prog) : "memory");
                }
                reported = cur;
                const int lead = (int)(reported * 128u) - (int)(gsum - base);
                int D = PACE_D0 - ((PACE_SL * lead + 64) >> 7);
                *depth = D < PACE_DMIN ? PACE_DMIN : D;
                if (!go && (int)(gsum - base) >= (int)((ADDS - WO_GATE) * 128u)) {
                    go = true;
                    *reinterpret_cast<volatile unsigned*>(sgen + OFF_GO) = 1;
                }
                if (++n > SPIN_LIMIT) __trap();
            }
            while (!go) {
                unsigned gsum;
                asm volatile("ld.relaxed.gpu.global.u32 %0, [%1];" : "=r"(gsum) : "l"(&g_prog) : "memory");
                if ((int)(gsum - base) >= (int)((ADDS - WO_GATE) * 128u)) break;
                if (++n > SPIN_LIMIT) __trap();
            }
            *reinterpret_cast<volatile unsigned*>(sgen + OFF_GO) = 1;
        }
    } else {
        const int g  = lane >> 2;
        const int t  = lane & 3;
        const int gs = warp >> 2;
        const int wi = warp & 3;
        const int grp = br * 2 + r;

        uint32_t xb[3][2];
        {
            const uint32_t* xw = reinterpret_cast<const uint32_t*>(p.x[br] + (g & 1) * DM + 320 * r + 16 * wi + 2 * t);
#pragma unroll
            for (int ii = 0; ii < 3; ++ii) {
                const int i = gs + 2 * ii;
                if (i < N_WQ) { xb[ii][0] = __ldg(xw + 32 * i); xb[ii][1] = __ldg(xw + 32 * i + 4); }
                else { xb[ii][0] = 0; xb[ii][1] = 0; }
            }
        }
        unsigned epoch = 0;
        if (tid == 0) epoch = *reinterpret_cast<volatile unsigned*>(&g_epoch[grp]);

        uint32_t koff[3], voff[3];
        {
            const int rowk = 16 * wi + (lane & 7) + 8 * ((lane >> 3) & 1), hik = lane >> 4;
            const int rowv = 16 * wi + (lane & 7) + 8 * (lane >> 4),       hiv = (lane >> 3) & 1;
#pragma unroll
            for (int sg = 0; sg < 3; ++sg) {
                const int lk = 3 * rowk + sg, lv = 3 * rowv + sg;
                koff[sg] = lk * 128 + ((hik ^ (lk & 7)) << 4);
                voff[sg] = lv * 128 + ((hiv ^ (lv & 7)) << 4);
            }
        }

        cluster_arrive();
        cluster_wait();

        float acc[12][4];
#pragma unroll
        for (int mt = 0; mt < 12; ++mt) { acc[mt][0] = acc[mt][1] = acc[mt][2] = acc[mt][3] = 0.f; }

#pragma unroll
        for (int ii = 0; ii < 3; ++ii) {
            const int i = gs + 2 * ii;
            if (i < N_WQ) {
                mbar_wait(fullb + i * 8, 0);
                if (lane == 0 && wi == 0 && (i == 0 || i == 4)) TS(i == 0 ? 1 : 2);
                pv_step(acc, ring + i * SLOT_BYTES, voff, xb[ii][0], xb[ii][1]);
                __syncwarp();
                if (lane == 0) mbar_arrive(emptb + i * 8);
            }
        }
        float* part = reinterpret_cast<float*>(sgen + OFF_PART);
        float* qown = reinterpret_cast<float*>(sgen + OFF_QOWN);
        float* qpeer = reinterpret_cast<float*>(sgen + OFF_QPEER);
        {
            float* dst = part + (warp * 2 + (t & 1)) * QP_STRIDE_B + g + 8 * (t >> 1);
#pragma unroll
            for (int mt = 0; mt < 12; ++mt) {
                const float v = sel4(t, acc[mt][0], acc[mt][1], acc[mt][2], acc[mt][3]);
                dst[16 * mt] = v;
            }
            if (tid == 0) *reinterpret_cast<unsigned*>(sgen + OFF_EPOCH) = epoch;
        }
        cons_sync();
        if (tid < DH) {
            float own = 0.f, oth = 0.f;
#pragma unroll
            for (int w = 0; w < 8; ++w) {
                own += part[(w * 2 + r) * QP_STRIDE_B + tid];
                oth += part[(w * 2 + (r ^ 1)) * QP_STRIDE_B + tid];
            }
            qown[tid] = own;
            st_async_b32(mapa(sbase + OFF_QPEER + tid * 4, r ^ 1), __float_as_uint(oth), mapa(xqb, r ^ 1));
        }
        cons_sync();
        mbar_wait_cluster(xqb, 0);
        epoch = *reinterpret_cast<volatile unsigned*>(sgen + OFF_EPOCH);

        uint32_t qb[12][2];
#pragma unroll
        for (int s = 0; s < 12; ++s) {
            const int c = 16 * s + 2 * t;
            qb[s][0] = pack_bf16(qown[c] + qpeer[c], qown[c + 1] + qpeer[c + 1]);
            qb[s][1] = pack_bf16(qown[c + 8] + qpeer[c + 8], qown[c + 9] + qpeer[c + 9]);
        }

        auto pub_addr = [&](int q) {
            const int o = (t & 1) * 320 + 16 * (warp + 8 * q) + g + 8 * (t >> 1);
            const int red = (o * 3277) >> 16;
            return g_part + ((size_t)(grp * NH + red) * NH + h) * 20 + (o - 20 * red);
        };
        auto prewrite = [&]() {
#pragma unroll
            for (int q = 0; q < 3; ++q)
                if (q < 2 || warp < 4)
                    asm volatile("st.relaxed.gpu.global.b64 [%0], %1;" ::"l"(pub_addr(q)), "l"((unsigned long long)epoch << 32) : "memory");
        };
        prewrite();
        if (tid == 0) TS(3);
#pragma unroll
        for (int mt = 0; mt < 12; ++mt) { acc[mt][0] = acc[mt][1] = acc[mt][2] = acc[mt][3] = 0.f; }
        const float sc = 0.07216878364870322f * 1.4426950408889634f;
        float m = -INFINITY, l = 0.f;

#pragma unroll 1
        for (int jj = 0; jj < N_PAIR / 2; ++jj) {
            const int iK = T_KV0 + 2 * (2 * jj + gs);
            const int iV = iK + 1;
            const int sK = iK & (NSLOT - 1), sV = iV & (NSLOT - 1);

            mbar_wait(fullb + sK * 8, (iK >> 3) & 1);
            float cA[4] = {0.f, 0.f, 0.f, 0.f}, cB[4] = {0.f, 0.f, 0.f, 0.f};
            {
                const uint32_t kt = ring + sK * SLOT_BYTES;
#pragma unroll
                for (int s = 0; s < 12; s += 2) {
                    uint32_t a0[4], a1[4];
                    ldsm4(a0, (kt + koff[s >> 2]) ^ ((s & 3) << 5));
                    ldsm4(a1, (kt + koff[(s + 1) >> 2]) ^ (((s + 1) & 3) << 5));
                    mma16816(cA, a0, qb[s][0], qb[s][1]);
                    mma16816(cB, a1, qb[s + 1][0], qb[s + 1][1]);
                }
            }
            __syncwarp();
            if (lane == 0) mbar_arrive(emptb + sK * 8);

            const float s0 = cA[0] + cB[0];
            const float s1 = cA[2] + cB[2];
            float bm = fmaxf(s0, s1);
            bm = fmaxf(bm, __shfl_xor_sync(0xffffffffu, bm, 4));
            bm = fmaxf(bm, __shfl_xor_sync(0xffffffffu, bm, 8));
            bm = fmaxf(bm, __shfl_xor_sync(0xffffffffu, bm, 16));
            if (bm > m) {
                const float f = ex2((m - bm) * sc);
                l *= f;
#pragma unroll
                for (int mt = 0; mt < 12; ++mt) { acc[mt][0] *= f; acc[mt][2] *= f; }
                m = bm;
            }
            const float ms = m * sc;
            const float p0 = ex2(fmaf(s0, sc, -ms));
            const float p1 = ex2(fmaf(s1, sc, -ms));
            l += p0 + p1;
            const uint32_t pk = pack_bf16(p0, p1);
            const uint32_t u = __shfl_sync(0xffffffffu, pk, 8 * t);
            const uint32_t v = __shfl_sync(0xffffffffu, pk, 8 * t + 4);
            const uint32_t b0 = __byte_perm(u, v, 0x5410);
            const uint32_t b1 = __byte_perm(u, v, 0x7632);

            mbar_wait(fullb + sV * 8, (iV >> 3) & 1);
            pv_step(acc, ring + sV * SLOT_BYTES, voff, b0, b1);
            __syncwarp();
            if (lane == 0) mbar_arrive(emptb + sV * 8);
        }

        if (tid == 128) {
            TS(4);
            asm volatile("red.relaxed.gpu.global.add.u32 [%0], 1;" ::"l"(&g_done[grp]) : "memory");
        }
        l += __shfl_xor_sync(0xffffffffu, l, 4);
        l += __shfl_xor_sync(0xffffffffu, l, 8);
        l += __shfl_xor_sync(0xffffffffu, l, 16);
        float* ml = reinterpret_cast<float*>(sgen + OFF_ML);
        if (t < 2) {
            float* dst = part + warp * DH + g + 8 * t;
#pragma unroll
            for (int mt = 0; mt < 12; ++mt) dst[16 * mt] = t ? acc[mt][2] : acc[mt][0];
        }
        if (lane == 0) { ml[warp * 2] = m; ml[warp * 2 + 1] = l; }
        part_arrive();

        unsigned long long* pub[3];
#pragma unroll
        for (int q = 0; q < 3; ++q) {
            pub[q] = pub_addr(q);
            asm volatile("" : "+l"(pub[q]));
        }
        const unsigned long long* src = g_part + (size_t)(grp * NH + h) * 640 + tid;
        const int oj = 20 * h + (tid >> 3);
        __nv_bfloat16* dsto = p.out + (oj >= 320 ? 2 * DM - 320 : 0) + br * DM + r * 320 + oj;
        const unsigned int* donep = &g_done[grp];
        asm volatile("" : "+l"(src), "+l"(dsto), "+l"(donep));

        uint32_t woff[3][2];
        {
            const int rowt = (lane & 7) + 8 * (lane >> 4), hit = (lane >> 3) & 1;
#pragma unroll
            for (int q = 0; q < 3; ++q) {
                const int mt = warp + 8 * q;
#pragma unroll
                for (int kk = 0; kk < 2; ++kk) {
                    const int line = 5 * (16 * kk + rowt) + (mt >> 2);
                    woff[q][kk] = ring + line * 128 + (((2 * (mt & 3) + hit) ^ (line & 7)) << 4);
                }
            }
        }
        mbar_wait_cluster(xob, 0);
        if (tid == 0) TS(6);
        float oc[3][2][4];
#pragma unroll
        for (int q = 0; q < 3; ++q)
#pragma unroll
            for (int kk = 0; kk < 2; ++kk) { oc[q][kk][0] = oc[q][kk][1] = oc[q][kk][2] = oc[q][kk][3] = 0.f; }
        {
            const uint32_t* obuf = reinterpret_cast<const uint32_t*>(sgen + OFF_OBUF);
            const uint4* os = reinterpret_cast<const uint4*>(obuf + (g & 1) * OB_STRIDE + 4 * t);
            uint4 b[N_WO];
#pragma unroll
            for (int i = 0; i < N_WO; ++i) b[i] = os[4 * i];
            uint32_t a[2][3][2][4];
            const bool three = warp < 4;
#pragma unroll
            for (int i = 0; i <= N_WO; ++i) {
                if (i < N_WO) {
                    const uint32_t so = ((T_WO0 + i) & (NSLOT - 1)) * SLOT_BYTES;
                    mbar_wait(wob + i * 8, 0);
#pragma unroll
                    for (int q = 0; q < 2; ++q) {
                        ldsm4t(a[i & 1][q][0], woff[q][0] + so);
                        ldsm4t(a[i & 1][q][1], woff[q][1] + so);
                    }
                    if (three) { ldsm4t(a[i & 1][2][0], woff[2][0] + so); ldsm4t(a[i & 1][2][1], woff[2][1] + so); }
                }
                if (i > 0) {
                    const int j = i - 1;
#pragma unroll
                    for (int q = 0; q < 2; ++q) {
                        mma16816(oc[q][0], a[j & 1][q][0], b[j].x, b[j].y);
                        mma16816(oc[q][1], a[j & 1][q][1], b[j].z, b[j].w);
                    }
                    if (three) {
                        mma16816(oc[2][0], a[j & 1][2][0], b[j].x, b[j].y);
                        mma16816(oc[2][1], a[j & 1][2][1], b[j].z, b[j].w);
                    }
                }
            }
        }
        if (tid == 0) TS(7);
        const unsigned tag = epoch + 1u;
#pragma unroll
        for (int q = 0; q < 3; ++q) {
            const float v = sel4(t, oc[q][0][0] + oc[q][1][0], oc[q][0][1] + oc[q][1][1],
                                    oc[q][0][2] + oc[q][1][2], oc[q][0][3] + oc[q][1][3]);
            const unsigned long long w = ((unsigned long long)tag << 32) | __float_as_uint(v);
            if (q < 2 || warp < 4)
                asm volatile("st.relaxed.gpu.global.b64 [%0], %1;" ::"l"(pub[q]), "l"(w) : "memory");
        }
        if (tid == 0) TS(9);
        if (tid < 160) {
            float v[4] = {0.f, 0.f, 0.f, 0.f};
            {
                unsigned n = 0, c;
                bool have[4] = {false, false, false, false};
                asm volatile("ld.relaxed.gpu.global.u32 %0, [%1];" : "=r"(c) : "l"(donep) : "memory");
                while (true) {
                    unsigned long long w[4] = {0ull, 0ull, 0ull, 0ull};
#pragma unroll
                    for (int i = 0; i < 4; ++i)
                        if (!have[i]) asm volatile("ld.relaxed.gpu.global.b64 %0, [%1];" : "=l"(w[i]) : "l"(src + i * 160) : "memory");
#pragma unroll
                    for (int i = 0; i < 4; ++i)
                        if (!have[i] && (unsigned)(w[i] >> 32) == tag) { have[i] = true; v[i] = __uint_as_float((unsigned)w[i]); }
                    if (__all_sync(0xffffffffu, have[0] && have[1] && have[2] && have[3])) break;
                    while ((int)(c - tag * NH) < 0) {
                        __nanosleep(300);
                        asm volatile("ld.relaxed.gpu.global.u32 %0, [%1];" : "=r"(c) : "l"(donep) : "memory");
                        if (++n > SPIN_LIMIT) __trap();
                    }
                    if (++n > SPIN_LIMIT) __trap();
                }
            }
            float* red = reinterpret_cast<float*>(sgen + OFF_PART);
#pragma unroll
            for (int i = 0; i < 4; ++i) red[tid + 160 * i] = v[i];
            asm volatile("bar.sync 3, 160;" ::: "memory");
            const int j = tid >> 3, s = tid & 7;
#pragma unroll
            for (int i = 0; i < 4; ++i) v[i] = red[(4 * s + i) * 20 + j];
            float sum = (v[0] + v[1]) + (v[2] + v[3]);
            sum += __shfl_xor_sync(0xffffffffu, sum, 1);
            sum += __shfl_xor_sync(0xffffffffu, sum, 2);
            sum += __shfl_xor_sync(0xffffffffu, sum, 4);
            if (s == 0) *dsto = __float2bfloat16(sum);
            if (tid == 0) { TS(8);
            }
            if (h == 0 && tid == 0) *reinterpret_cast<volatile unsigned*>(&g_epoch[grp]) = tag;
        }
    }
}

typedef CUresult (*EncodeTiledFn)(CUtensorMap*, CUtensorMapDataType, cuuint32_t, void*, const cuuint64_t*,
                                  const cuuint64_t*, const cuuint32_t*, const cuuint32_t*, CUtensorMapInterleave,
                                  CUtensorMapSwizzle, CUtensorMapL2promotion, CUtensorMapFloatOOBfill);

bool encode(EncodeTiledFn fn, CUtensorMap* tm, const void* ptr, int rank, const cuuint64_t* dims,
            const cuuint64_t* strides, const cuuint32_t* box) {
    const cuuint32_t es[3] = {1, 1, 1};
    CUresult rc = fn(tm, CU_TENSOR_MAP_DATA_TYPE_BFLOAT16, (cuuint32_t)rank, const_cast<void*>(ptr), dims, strides, box, es,
                     CU_TENSOR_MAP_INTERLEAVE_NONE, CU_TENSOR_MAP_SWIZZLE_128B, CU_TENSOR_MAP_L2_PROMOTION_L2_128B,
                     CU_TENSOR_MAP_FLOAT_OOB_FILL_NONE);
    if (rc != CUDA_SUCCESS) { fprintf(stderr, "cuTensorMapEncodeTiled failed: %d\n", (int)rc); return false; }
    return true;
}

}

extern "C" void kernel_launch(void* const* d_in, const int* in_sizes, int n_in, void* d_out, int out_size) {
    (void)in_sizes; (void)n_in; (void)out_size;
    static EncodeTiledFn fn = nullptr;
    if (!fn) {
        void* f = nullptr;
        cudaDriverEntryPointQueryResult qr;
        if (cudaGetDriverEntryPoint("cuTensorMapEncodeTiled", &f, cudaEnableDefault, &qr) != cudaSuccess || !f) {
            fprintf(stderr, "cuTensorMapEncodeTiled not available\n");
            return;
        }
        fn = (EncodeTiledFn)f;
        cudaFuncSetAttribute(fused_decode_kernel, cudaFuncAttributeMaxDynamicSharedMemorySize, SMEM_BYTES);
    }
    Params p;
    for (int b = 0; b < 2; ++b) {
        void* const* in = d_in + 5 * b;
        p.x[b] = (const __nv_bfloat16*)in[0];
        {
            const cuuint64_t dims[2] = {64, (cuuint64_t)2 * NH * SK * 3};
            const cuuint64_t strides[1] = {128};
            const cuuint32_t box[2] = {64, 192};
            if (!encode(fn, &p.k[b], in[1], 2, dims, strides, box)) return;
            if (!encode(fn, &p.v[b], in[2], 2, dims, strides, box)) return;
        }
        {
            const cuuint64_t dims[3] = {64, 96, 640};
            const cuuint64_t strides[2] = {128, 12288};
            const cuuint32_t box[3] = {64, 3, 64};
            if (!encode(fn, &p.wq[b], in[3], 3, dims, strides, box)) return;
        }
        {
            const cuuint64_t dims[3] = {64, 10, 6144};
            const cuuint64_t strides[2] = {128, 1280};
            const cuuint32_t box[3] = {64, 5, 32};
            if (!encode(fn, &p.wo[b], in[4], 3, dims, strides, box)) return;
        }
    }
    p.out = (__nv_bfloat16*)d_out;
    fused_decode_kernel<<<128, NTHREADS, SMEM_BYTES>>>(p);
}
```

```cpp
#include <cuda_runtime.h>
#include <cuda_bf16.h>
#include <cuda.h>
#include <stdint.h>
#include <stdio.h>

namespace {

constexpr int DM = 640;
constexpr int NH = 32;
constexpr int SK = 8192;
constexpr int DH = 192;

constexpr int NSLOT      = 8;
constexpr int SLOT_BYTES = 24576;
constexpr int N_WQ   = 5;
constexpr int N_PAIR = SK / 64;
constexpr int N_WO   = 6;
constexpr int T_KV0  = N_WQ;
constexpr int T_WO0  = N_WQ + 2 * N_PAIR;
constexpr int N_TILES = T_WO0 + N_WO;
constexpr int WO_BYTES = 32 * 640;

constexpr int NTHREADS = 320;

constexpr int QP_STRIDE_B = 208;
constexpr int OB_STRIDE = 112;
constexpr int OFF_RING  = 0;
constexpr int OFF_PART  = NSLOT * SLOT_BYTES;
constexpr int OFF_QOWN  = OFF_PART + 8 * 2 * QP_STRIDE_B * 4;
constexpr int OFF_QPEER = OFF_QOWN + DH * 4;
constexpr int OFF_OBUF  = OFF_QPEER + DH * 4;
constexpr int OFF_ML    = OFF_OBUF + 2 * OB_STRIDE * 4;
constexpr int OFF_BARS  = OFF_ML + 8 * 2 * 4;
constexpr int OFF_EPOCH = OFF_BARS + (2 * NSLOT + 2 + N_WO) * 8;
constexpr int OFF_PROG  = OFF_EPOCH + 4;
constexpr int OFF_DEPTH = OFF_EPOCH + 8;
constexpr int OFF_GO    = OFF_EPOCH + 12;
constexpr int SMEM_USED = OFF_EPOCH + 16;
constexpr int SMEM_BYTES = SMEM_USED + 1024;

struct alignas(64) Params {
    CUtensorMap k[2];
    CUtensorMap v[2];
    CUtensorMap wq[2];
    CUtensorMap wo[2];
    const __nv_bfloat16* x[2];
    const __nv_bfloat16* kraw[2];
    const __nv_bfloat16* wqraw[2];
    const __nv_bfloat16* vraw[2];
    __nv_bfloat16* out;
};

__device__ unsigned long long g_part[2 * 2 * NH * 640];
__device__ unsigned int g_prog;
__device__ unsigned int g_epoch[4];
__device__ unsigned int g_done[4];

constexpr int PACE_D0 = 7, PACE_SL = 4, PACE_DMIN = 2;
constexpr unsigned PACE_TILES = T_WO0 - NSLOT + 1;
constexpr unsigned WO_GATE = 2;

#define PRE_OUT 1
#define EARLY_TM 1
#define EARLY_TM_WARP 6
#define EARLY_K 24576
#define EARLY_WQ 1
#define EARLY_WQ_WARP 7
constexpr unsigned SPIN_LIMIT = 1u << 24;

#define TS(i) do { } while (0)

__device__ __forceinline__ uint32_t smem_u32(const void* p) { return (uint32_t)__cvta_generic_to_shared(p); }

__device__ __forceinline__ void mbar_init(uint32_t bar, uint32_t cnt) {
    asm volatile("mbarrier.init.shared::cta.b64 [%0], %1;" ::"r"(bar), "r"(cnt) : "memory");
}
__device__ __forceinline__ void mbar_expect_tx(uint32_t bar, uint32_t bytes) {
    asm volatile("mbarrier.arrive.expect_tx.shared::cta.b64 _, [%0], %1;" ::"r"(bar), "r"(bytes) : "memory");
}
__device__ __forceinline__ void mbar_arrive(uint32_t bar) {
    asm volatile("mbarrier.arrive.shared::cta.b64 _, [%0];" ::"r"(bar) : "memory");
}
__device__ __forceinline__ bool mbar_try(uint32_t bar, uint32_t parity) {
    uint32_t ok;
    asm volatile("{\n.reg .pred p;\nmbarrier.try_wait.parity.shared::cta.b64 p, [%1], %2;\nselp.u32 %0, 1, 0, p;\n}"
                 : "=r"(ok) : "r"(bar), "r"(parity) : "memory");
    return ok != 0;
}
__device__ __forceinline__ bool mbar_test(uint32_t bar, uint32_t parity) {
    uint32_t ok;
    asm volatile("{\n.reg .pred p;\nmbarrier.test_wait.parity.shared::cta.b64 p, [%1], %2;\nselp.u32 %0, 1, 0, p;\n}"
                 : "=r"(ok) : "r"(bar), "r"(parity) : "memory");
    return ok != 0;
}
__device__ __forceinline__ bool mbar_try_cluster(uint32_t bar, uint32_t parity) {
    uint32_t ok;
    asm volatile("{\n.reg .pred p;\nmbarrier.try_wait.parity.acquire.cluster.shared::cta.b64 p, [%1], %2;\nselp.u32 %0, 1, 0, p;\n}"
                 : "=r"(ok) : "r"(bar), "r"(parity) : "memory");
    return ok != 0;
}
__device__ __forceinline__ void mbar_wait(uint32_t bar, uint32_t parity) {
    unsigned n = 0;
    while (!mbar_try(bar, parity)) { if (++n > SPIN_LIMIT) __trap(); }
}
__device__ __forceinline__ void mbar_wait_cluster(uint32_t bar, uint32_t parity) {
    unsigned n = 0;
    while (!mbar_try_cluster(bar, parity)) { if (++n > SPIN_LIMIT) __trap(); }
}
__device__ __forceinline__ void tma2d(uint32_t dst, const CUtensorMap* tm, int c0, int c1, uint32_t bar, uint64_t pol) {
    asm volatile("cp.async.bulk.tensor.2d.shared::cluster.global.mbarrier::complete_tx::bytes.L2::cache_hint"
                 " [%0], [%1, {%3, %4}], [%2], %5;"
                 ::"r"(dst), "l"(tm), "r"(bar), "r"(c0), "r"(c1), "l"(pol) : "memory");
}
__device__ __forceinline__ void tma3d(uint32_t dst, const CUtensorMap* tm, int c0, int c1, int c2, uint32_t bar, uint64_t pol) {
    asm volatile("cp.async.bulk.tensor.3d.shared::cluster.global.mbarrier::complete_tx::bytes.L2::cache_hint"
                 " [%0], [%1, {%3, %4, %5}], [%2], %6;"
                 ::"r"(dst), "l"(tm), "r"(bar), "r"(c0), "r"(c1), "r"(c2), "l"(pol) : "memory");
}
__device__ __forceinline__ void ldsm4(uint32_t (&a)[4], uint32_t addr) {
    asm volatile("ldmatrix.sync.aligned.m8n8.x4.shared.b16 {%0,%1,%2,%3}, [%4];"
                 : "=r"(a[0]), "=r"(a[1]), "=r"(a[2]), "=r"(a[3]) : "r"(addr) : "memory");
}
__device__ __forceinline__ void ldsm4t(uint32_t (&a)[4], uint32_t addr) {
    asm volatile("ldmatrix.sync.aligned.m8n8.x4.trans.shared.b16 {%0,%1,%2,%3}, [%4];"
                 : "=r"(a[0]), "=r"(a[1]), "=r"(a[2]), "=r"(a[3]) : "r"(addr) : "memory");
}
__device__ __forceinline__ void mma16816(float (&c)[4], const uint32_t (&a)[4], uint32_t b0, uint32_t b1) {
    asm volatile("mma.sync.aligned.m16n8k16.row.col.f32.bf16.bf16.f32 {%0,%1,%2,%3}, {%4,%5,%6,%7}, {%8,%9}, {%0,%1,%2,%3};"
                 : "+f"(c[0]), "+f"(c[1]), "+f"(c[2]), "+f"(c[3])
                 : "r"(a[0]), "r"(a[1]), "r"(a[2]), "r"(a[3]), "r"(b0), "r"(b1));
}
__device__ __forceinline__ float ex2(float x) {
    float y;
    asm("ex2.approx.ftz.f32 %0, %1;" : "=f"(y) : "f"(x));
    return y;
}
__device__ __forceinline__ float rcp(float x) {
    float y;
    asm("rcp.approx.ftz.f32 %0, %1;" : "=f"(y) : "f"(x));
    return y;
}
__device__ __forceinline__ uint32_t pack_bf16(float lo, float hi) {
    uint32_t r;
    asm("cvt.rn.bf16x2.f32 %0, %1, %2;" : "=r"(r) : "f"(hi), "f"(lo));
    return r;
}
__device__ __forceinline__ uint32_t mapa(uint32_t addr, uint32_t cta) {
    uint32_t r;
    asm("mapa.shared::cluster.u32 %0, %1, %2;" : "=r"(r) : "r"(addr), "r"(cta));
    return r;
}
__device__ __forceinline__ void st_async_b32(uint32_t raddr, uint32_t v, uint32_t rbar) {
    asm volatile("st.async.weak.shared::cluster.mbarrier::complete_tx::bytes.b32 [%0], %1, [%2];"
                 ::"r"(raddr), "r"(v), "r"(rbar) : "memory");
}
__device__ __forceinline__ void cons_sync() { asm volatile("bar.sync 1, 256;" ::: "memory"); }
__device__ __forceinline__ void part_arrive() { asm volatile("bar.arrive 2, 288;" ::: "memory"); }
__device__ __forceinline__ void part_sync() { asm volatile("bar.sync 2, 288;" ::: "memory"); }
__device__ __forceinline__ float sel4(int t, float a, float b, float c, float d) {
    const float lo = (t & 1) ? b : a, hi = (t & 1) ? d : c;
    return (t & 2) ? hi : lo;
}
__device__ __forceinline__ void cluster_arrive() { asm volatile("barrier.cluster.arrive.relaxed.aligned;" ::: "memory"); }
__device__ __forceinline__ void cluster_wait() { asm volatile("barrier.cluster.wait.acquire.aligned;" ::: "memory"); }

__device__ __forceinline__ void pv_step(float (&acc)[12][4], uint32_t tile_addr, const uint32_t (&voff)[3],
                                        uint32_t b0, uint32_t b1) {
#pragma unroll
    for (int mt = 0; mt < 12; ++mt) {
        uint32_t a[4];
        ldsm4t(a, (tile_addr + voff[mt >> 2]) ^ ((mt & 3) << 5));
        mma16816(acc[mt], a, b0, b1);
    }
}

__global__ void __cluster_dims__(2, 1, 1) __launch_bounds__(NTHREADS, 1)
fused_decode_kernel(const __grid_constant__ Params p) {
    extern __shared__ uint8_t smem_raw[];
    const uint32_t sbase = (smem_u32(smem_raw) + 1023u) & ~1023u;
    uint8_t* sgen = smem_raw + (sbase - smem_u32(smem_raw));

    const int tid  = threadIdx.x;
    const int warp = tid >> 5;
    const int lane = tid & 31;
    const int r    = blockIdx.x & 1;
    const int cl   = blockIdx.x >> 1;
    const int br   = cl >> 5;
    const int h    = cl & 31;

    if (warp == EARLY_TM_WARP && lane < 3) {
        const CUtensorMap* tm = lane == 0 ? &p.wq[br] : lane == 1 ? &p.k[br] : &p.v[br];
        asm volatile("prefetch.tensormap [%0];" ::"l"(tm) : "memory");
    }
    if (tid == 288) {
        const size_t off = (size_t)(r * NH + h) * SK * DH;
        asm volatile("cp.async.bulk.prefetch.L2.global [%0], %1;" ::"l"(p.kraw[br] + off), "r"(EARLY_K) : "memory");
    }
    if (warp == EARLY_WQ_WARP) {
        const char* w0 = reinterpret_cast<const char*>(p.wqraw[br] + (size_t)(320 * r) * (NH * DH) + h * DH);
#pragma unroll
        for (int k = 0; k < 6 * EARLY_WQ; ++k) {
            const int ln = 32 * k + lane;
            const int row = (ln * 21846) >> 16;
            asm volatile("prefetch.global.L2 [%0];" ::"l"(w0 + (size_t)row * (NH * DH * 2) + (ln - 3 * row) * 128));
        }
    }
    const uint32_t ring  = sbase + OFF_RING;
    const uint32_t fullb = sbase + OFF_BARS;
    const uint32_t emptb = fullb + NSLOT * 8;
    const uint32_t xqb   = emptb + NSLOT * 8;
    const uint32_t xob   = xqb + 8;
    const uint32_t wob   = xob + 8;

    if (warp == 8) {
        uint64_t pol = 0;
        const int kv_line0 = (r * NH + h) * SK * 3;
        auto issue = [&](int i) {
            const int s = i & (NSLOT - 1);
            const uint32_t dst = ring + s * SLOT_BYTES;
            const uint32_t bar = fullb + s * 8;
            if (i < T_KV0) {
                mbar_expect_tx(bar, SLOT_BYTES);
                tma3d(dst, &p.wq[br], 0, 3 * h, 320 * r + 64 * i, bar, pol);
            } else if (i < T_WO0) {
                const int j = i - T_KV0;
                mbar_expect_tx(bar, SLOT_BYTES);
                tma2d(dst, (j & 1) ? &p.v[br] : &p.k[br], 0, kv_line0 + (j >> 1) * 192, bar, pol);
            } else {
                const uint32_t wb = wob + (i - T_WO0) * 8;
                mbar_expect_tx(wb, WO_BYTES);
                tma3d(dst, &p.wo[br], 0, 5 * r, DH * h + 32 * (i - T_WO0), wb, pol);
            }
        };
        if (lane == 0) {
            TS(0);
            for (int s = 0; s < NSLOT; ++s) { mbar_init(fullb + s * 8, 1); mbar_init(emptb + s * 8, 4); }
            *reinterpret_cast<volatile unsigned*>(sgen + OFF_PROG) = 0;
            *reinterpret_cast<volatile int*>(sgen + OFF_DEPTH) = NSLOT;
            *reinterpret_cast<volatile unsigned*>(sgen + OFF_GO) = 0;
            mbar_init(xqb, 1);
            mbar_init(xob, 2);
            for (int k = 0; k < N_WO; ++k) mbar_init(wob + k * 8, 1);
            asm volatile("fence.mbarrier_init.release.cluster;" ::: "memory");
            asm volatile("createpolicy.fractional.L2::evict_first.b64 %0, 1.0;" : "=l"(pol));
            for (int i = 0; i < NSLOT; ++i) issue(i);
            mbar_expect_tx(xqb, DH * 4);
            mbar_expect_tx(xob, DH * 2);
        }
        __syncwarp();
        asm volatile("bar.arrive 4, 64;" ::: "memory");
        cluster_arrive();
        cluster_wait();
        if (lane == 0) {
            volatile unsigned* prog = reinterpret_cast<volatile unsigned*>(sgen + OFF_PROG);
            volatile int* depth = reinterpret_cast<volatile int*>(sgen + OFF_DEPTH);
            for (int i = NSLOT; i < N_TILES; ++i) {
                mbar_wait(emptb + (i & (NSLOT - 1)) * 8, ((i >> 3) & 1) ^ 1);
                *prog = i - NSLOT + 1;
                if (i < T_WO0) {
                    unsigned n = 0;
                    while (true) {
                        const int D = *depth;
                        if (D >= NSLOT) break;
                        const int x = i - D;
                        if (mbar_test(emptb + (x & (NSLOT - 1)) * 8, (x >> 3) & 1)) break;
                        if (++n > SPIN_LIMIT) __trap();
                    }
                }
                if (i == T_WO0) {
                    unsigned n = 0;
                    while (*reinterpret_cast<volatile unsigned*>(sgen + OFF_GO) == 0) { if (++n > SPIN_LIMIT) __trap(); }
                }
                issue(i);
            }
        }
        __syncwarp();
        {
            const float* part = reinterpret_cast<const float*>(sgen + OFF_PART);
            const float* ml   = reinterpret_cast<const float*>(sgen + OFF_ML);
            uint32_t* obuf    = reinterpret_cast<uint32_t*>(sgen + OFF_OBUF);
            const float sc = 0.07216878364870322f * 1.4426950408889634f;
            const int u = lane & 7;
            const int pos0 = r * OB_STRIDE + 16 * (lane >> 4) + 4 * (u & 3) + 2 * ((lane >> 3) & 1) + (u >> 2);
            const uint32_t ra = mapa(sbase + OFF_OBUF + pos0 * 4, r ^ 1), rb = mapa(xob, r ^ 1);
            part_sync();
            const float4 ml0 = *reinterpret_cast<const float4*>(ml), ml1 = *reinterpret_cast<const float4*>(ml + 4);
            const float4 ml2 = *reinterpret_cast<const float4*>(ml + 8), ml3 = *reinterpret_cast<const float4*>(ml + 12);
            float2 pv[8][3];
#pragma unroll
            for (int w = 0; w < 8; ++w)
#pragma unroll
                for (int k = 0; k < 3; ++k) pv[w][k] = *reinterpret_cast<const float2*>(part + w * DH + 2 * (lane + 32 * k));
            const float mw[8] = {ml0.x, ml0.z, ml1.x, ml1.z, ml2.x, ml2.z, ml3.x, ml3.z};
            const float lw[8] = {ml0.y, ml0.w, ml1.y, ml1.w, ml2.y, ml2.w, ml3.y, ml3.w};
            const float M = fmaxf(fmaxf(fmaxf(mw[0], mw[1]), fmaxf(mw[2], mw[3])), fmaxf(fmaxf(mw[4], mw[5]), fmaxf(mw[6], mw[7])));
            float L = 0.f, o[3][2] = {{0.f, 0.f}, {0.f, 0.f}, {0.f, 0.f}};
#pragma unroll
            for (int w = 0; w < 8; ++w) {
                const float f = ex2((mw[w] - M) * sc);
                L = fmaf(f, lw[w], L);
#pragma unroll
                for (int k = 0; k < 3; ++k) {
                    o[k][0] = fmaf(f, pv[w][k].x, o[k][0]);
                    o[k][1] = fmaf(f, pv[w][k].y, o[k][1]);
                }
            }
            const float inv = rcp(L);
#pragma unroll
            for (int k = 0; k < 3; ++k) {
                const uint32_t ob = pack_bf16(o[k][0] * inv, o[k][1] * inv);
                obuf[pos0 + 32 * k] = ob;
                st_async_b32(ra + 128 * k, ob, rb);
            }
            __syncwarp();
            if (lane == 0) { mbar_arrive(xob); TS(5); }
        }
    } else if (warp == 9) {
        cluster_arrive();
        cluster_wait();
        asm volatile("bar.sync 4, 64;" ::: "memory");
        if (lane == 0) {
            constexpr unsigned ADDS = PACE_TILES;
            volatile unsigned* prog = reinterpret_cast<volatile unsigned*>(sgen + OFF_PROG);
            volatile int* depth = reinterpret_cast<volatile int*>(sgen + OFF_DEPTH);
            const unsigned base = *reinterpret_cast<volatile unsigned*>(&g_epoch[br * 2 + r]) * (128u * ADDS);
            unsigned reported = 0, n = 0;
            bool go = false;
            while (reported < ADDS) {
                unsigned cur = *prog;
                cur = cur < ADDS ? cur : ADDS;
                const unsigned delta = cur - reported;
                unsigned gsum;
                if (delta) {
                    asm volatile("atom.relaxed.gpu.global.add.u32 %0, [%1], %2;" : "=r"(gsum) : "l"(&g_prog), "r"(delta) : "memory");
                    gsum += delta;
                } else {
                    asm volatile("ld.relaxed.gpu.global.u32 %0, [%1];" : "=r"(gsum) : "l"(&g_prog) : "memory");
                }
                reported = cur;
                const int lead = (int)(reported * 128u) - (int)(gsum - base);
                int D = PACE_D0 - ((PACE_SL * lead + 64) >> 7);
                *depth = D < PACE_DMIN ? PACE_DMIN : D;
                if (!go && (int)(gsum - base) >= (int)((ADDS - WO_GATE) * 128u)) {
                    go = true;
                    *reinterpret_cast<volatile unsigned*>(sgen + OFF_GO) = 1;
                }
                if (++n > SPIN_LIMIT) __trap();
            }
            while (!go) {
                unsigned gsum;
                asm volatile("ld.relaxed.gpu.global.u32 %0, [%1];" : "=r"(gsum) : "l"(&g_prog) : "memory");
                if ((int)(gsum - base) >= (int)((ADDS - WO_GATE) * 128u)) break;
                if (++n > SPIN_LIMIT) __trap();
            }
            *reinterpret_cast<volatile unsigned*>(sgen + OFF_GO) = 1;
        }
    } else {
        const int g  = lane >> 2;
        const int t  = lane & 3;
        const int gs = warp >> 2;
        const int wi = warp & 3;
        const int grp = br * 2 + r;

        uint32_t xb[3][2];
        {
            const uint32_t* xw = reinterpret_cast<const uint32_t*>(p.x[br] + (g & 1) * DM + 320 * r + 16 * wi + 2 * t);
#pragma unroll
            for (int ii = 0; ii < 3; ++ii) {
                const int i = gs + 2 * ii;
                if (i < N_WQ) { xb[ii][0] = __ldg(xw + 32 * i); xb[ii][1] = __ldg(xw + 32 * i + 4); }
                else { xb[ii][0] = 0; xb[ii][1] = 0; }
            }
        }
        unsigned epoch = 0;
        if (tid == 0) epoch = *reinterpret_cast<volatile unsigned*>(&g_epoch[grp]);

        uint32_t koff[3], voff[3];
        {
            const int rowk = 16 * wi + (lane & 7) + 8 * ((lane >> 3) & 1), hik = lane >> 4;
            const int rowv = 16 * wi + (lane & 7) + 8 * (lane >> 4),       hiv = (lane >> 3) & 1;
#pragma unroll
            for (int sg = 0; sg < 3; ++sg) {
                const int lk = 3 * rowk + sg, lv = 3 * rowv + sg;
                koff[sg] = lk * 128 + ((hik ^ (lk & 7)) << 4);
                voff[sg] = lv * 128 + ((hiv ^ (lv & 7)) << 4);
            }
        }

        cluster_arrive();
        cluster_wait();

        float acc[12][4];
#pragma unroll
        for (int mt = 0; mt < 12; ++mt) { acc[mt][0] = acc[mt][1] = acc[mt][2] = acc[mt][3] = 0.f; }

#pragma unroll
        for (int ii = 0; ii < 3; ++ii) {
            const int i = gs + 2 * ii;
            if (i < N_WQ) {
                mbar_wait(fullb + i * 8, 0);
                if (lane == 0 && wi == 0 && (i == 0 || i == 4)) TS(i == 0 ? 1 : 2);
                pv_step(acc, ring + i * SLOT_BYTES, voff, xb[ii][0], xb[ii][1]);
                __syncwarp();
                if (lane == 0) mbar_arrive(emptb + i * 8);
            }
        }
        float* part = reinterpret_cast<float*>(sgen + OFF_PART);
        float* qown = reinterpret_cast<float*>(sgen + OFF_QOWN);
        float* qpeer = reinterpret_cast<float*>(sgen + OFF_QPEER);
        {
            float* dst = part + (warp * 2 + (t & 1)) * QP_STRIDE_B + g + 8 * (t >> 1);
#pragma unroll
            for (int mt = 0; mt < 12; ++mt) {
                const float v = sel4(t, acc[mt][0], acc[mt][1], acc[mt][2], acc[mt][3]);
                dst[16 * mt] = v;
            }
            if (tid == 0) *reinterpret_cast<unsigned*>(sgen + OFF_EPOCH) = epoch;
        }
        cons_sync();
        if (tid < DH) {
            float own = 0.f, oth = 0.f;
#pragma unroll
            for (int w = 0; w < 8; ++w) {
                own += part[(w * 2 + r) * QP_STRIDE_B + tid];
                oth += part[(w * 2 + (r ^ 1)) * QP_STRIDE_B + tid];
            }
            qown[tid] = own;
            st_async_b32(mapa(sbase + OFF_QPEER + tid * 4, r ^ 1), __float_as_uint(oth), mapa(xqb, r ^ 1));
        }
        cons_sync();
        mbar_wait_cluster(xqb, 0);
        epoch = *reinterpret_cast<volatile unsigned*>(sgen + OFF_EPOCH);

        uint32_t qb[12][2];
#pragma unroll
        for (int s = 0; s < 12; ++s) {
            const int c = 16 * s + 2 * t;
            qb[s][0] = pack_bf16(qown[c] + qpeer[c], qown[c + 1] + qpeer[c + 1]);
            qb[s][1] = pack_bf16(qown[c + 8] + qpeer[c + 8], qown[c + 9] + qpeer[c + 9]);
        }

        auto pub_addr = [&](int q) {
            const int o = (t & 1) * 320 + 16 * (warp + 8 * q) + g + 8 * (t >> 1);
            const int red = (o * 3277) >> 16;
            return g_part + ((size_t)(grp * NH + red) * NH + h) * 20 + (o - 20 * red);
        };
        auto prewrite = [&]() {
#pragma unroll
            for (int q = 0; q < 3; ++q)
                if (q < 2 || warp < 4)
                    asm volatile("st.relaxed.gpu.global.b64 [%0], %1;" ::"l"(pub_addr(q)), "l"((unsigned long long)epoch << 32) : "memory");
        };
        prewrite();
        if (tid < 160 && (tid & 7) == 0) {
            const int oq = 20 * h + (tid >> 3);
            p.out[(oq >= 320 ? 2 * DM - 320 : 0) + br * DM + r * 320 + oq] = __float2bfloat16(0.f);
        }
        if (tid == 0) TS(3);
#pragma unroll
        for (int mt = 0; mt < 12; ++mt) { acc[mt][0] = acc[mt][1] = acc[mt][2] = acc[mt][3] = 0.f; }
        const float sc = 0.07216878364870322f * 1.4426950408889634f;
        float m = -INFINITY, l = 0.f;

#pragma unroll 1
        for (int jj = 0; jj < N_PAIR / 2; ++jj) {
            const int iK = T_KV0 + 2 * (2 * jj + gs);
            const int iV = iK + 1;
            const int sK = iK & (NSLOT - 1), sV = iV & (NSLOT - 1);

            mbar_wait(fullb + sK * 8, (iK >> 3) & 1);
            float cA[4] = {0.f, 0.f, 0.f, 0.f}, cB[4] = {0.f, 0.f, 0.f, 0.f};
            {
                const uint32_t kt = ring + sK * SLOT_BYTES;
#pragma unroll
                for (int s = 0; s < 12; s += 2) {
                    uint32_t a0[4], a1[4];
                    ldsm4(a0, (kt + koff[s >> 2]) ^ ((s & 3) << 5));
                    ldsm4(a1, (kt + koff[(s + 1) >> 2]) ^ (((s + 1) & 3) << 5));
                    mma16816(cA, a0, qb[s][0], qb[s][1]);
                    mma16816(cB, a1, qb[s + 1][0], qb[s + 1][1]);
                }
            }
            __syncwarp();
            if (lane == 0) mbar_arrive(emptb + sK * 8);

            const float s0 = cA[0] + cB[0];
            const float s1 = cA[2] + cB[2];
            float bm = fmaxf(s0, s1);
            bm = fmaxf(bm, __shfl_xor_sync(0xffffffffu, bm, 4));
            bm = fmaxf(bm, __shfl_xor_sync(0xffffffffu, bm, 8));
            bm = fmaxf(bm, __shfl_xor_sync(0xffffffffu, bm, 16));
            if (bm > m) {
                const float f = ex2((m - bm) * sc);
                l *= f;
#pragma unroll
                for (int mt = 0; mt < 12; ++mt) { acc[mt][0] *= f; acc[mt][2] *= f; }
                m = bm;
            }
            const float ms = m * sc;
            const float p0 = ex2(fmaf(s0, sc, -ms));
            const float p1 = ex2(fmaf(s1, sc, -ms));
            l += p0 + p1;
            const uint32_t pk = pack_bf16(p0, p1);
            const uint32_t u = __shfl_sync(0xffffffffu, pk, 8 * t);
            const uint32_t v = __shfl_sync(0xffffffffu, pk, 8 * t + 4);
            const uint32_t b0 = __byte_perm(u, v, 0x5410);
            const uint32_t b1 = __byte_perm(u, v, 0x7632);

            mbar_wait(fullb + sV * 8, (iV >> 3) & 1);
            pv_step(acc, ring + sV * SLOT_BYTES, voff, b0, b1);
            __syncwarp();
            if (lane == 0) mbar_arrive(emptb + sV * 8);
        }

        if (tid == 128) {
            TS(4);
            asm volatile("red.relaxed.gpu.global.add.u32 [%0], 1;" ::"l"(&g_done[grp]) : "memory");
        }
        l += __shfl_xor_sync(0xffffffffu, l, 4);
        l += __shfl_xor_sync(0xffffffffu, l, 8);
        l += __shfl_xor_sync(0xffffffffu, l, 16);
        float* ml = reinterpret_cast<float*>(sgen + OFF_ML);
        if (t < 2) {
            float* dst = part + warp * DH + g + 8 * t;
#pragma unroll
            for (int mt = 0; mt < 12; ++mt) dst[16 * mt] = t ? acc[mt][2] : acc[mt][0];
        }
        if (lane == 0) { ml[warp * 2] = m; ml[warp * 2 + 1] = l; }
        part_arrive();

        unsigned long long* pub[3];
#pragma unroll
        for (int q = 0; q < 3; ++q) {
            pub[q] = pub_addr(q);
            asm volatile("" : "+l"(pub[q]));
        }
        const unsigned long long* src = g_part + (size_t)(grp * NH + h) * 640 + tid;
        const int oj = 20 * h + (tid >> 3);
        __nv_bfloat16* dsto = p.out + (oj >= 320 ? 2 * DM - 320 : 0) + br * DM + r * 320 + oj;
        const unsigned int* donep = &g_done[grp];
        asm volatile("" : "+l"(src), "+l"(dsto), "+l"(donep));

        uint32_t woff[3][2];
        {
            const int rowt = (lane & 7) + 8 * (lane >> 4), hit = (lane >> 3) & 1;
#pragma unroll
            for (int q = 0; q < 3; ++q) {
                const int mt = warp + 8 * q;
#pragma unroll
                for (int kk = 0; kk < 2; ++kk) {
                    const int line = 5 * (16 * kk + rowt) + (mt >> 2);
                    woff[q][kk] = ring + line * 128 + (((2 * (mt & 3) + hit) ^ (line & 7)) << 4);
                }
            }
        }
        mbar_wait_cluster(xob, 0);
        if (tid == 0) TS(6);
        float oc[3][2][4];
#pragma unroll
        for (int q = 0; q < 3; ++q)
#pragma unroll
            for (int kk = 0; kk < 2; ++kk) { oc[q][kk][0] = oc[q][kk][1] = oc[q][kk][2] = oc[q][kk][3] = 0.f; }
        {
            const uint32_t* obuf = reinterpret_cast<const uint32_t*>(sgen + OFF_OBUF);
            const uint4* os = reinterpret_cast<const uint4*>(obuf + (g & 1) * OB_STRIDE + 4 * t);
            uint4 b[N_WO];
#pragma unroll
            for (int i = 0; i < N_WO; ++i) b[i] = os[4 * i];
            uint32_t a[2][3][2][4];
            const bool three = warp < 4;
#pragma unroll
            for (int i = 0; i <= N_WO; ++i) {
                if (i < N_WO) {
                    const uint32_t so = ((T_WO0 + i) & (NSLOT - 1)) * SLOT_BYTES;
                    mbar_wait(wob + i * 8, 0);
#pragma unroll
                    for (int q = 0; q < 2; ++q) {
                        ldsm4t(a[i & 1][q][0], woff[q][0] + so);
                        ldsm4t(a[i & 1][q][1], woff[q][1] + so);
                    }
                    if (three) { ldsm4t(a[i & 1][2][0], woff[2][0] + so); ldsm4t(a[i & 1][2][1], woff[2][1] + so); }
                }
                if (i > 0) {
                    const int j = i - 1;
#pragma unroll
                    for (int q = 0; q < 2; ++q) {
                        mma16816(oc[q][0], a[j & 1][q][0], b[j].x, b[j].y);
                        mma16816(oc[q][1], a[j & 1][q][1], b[j].z, b[j].w);
                    }
                    if (three) {
                        mma16816(oc[2][0], a[j & 1][2][0], b[j].x, b[j].y);
                        mma16816(oc[2][1], a[j & 1][2][1], b[j].z, b[j].w);
                    }
                }
            }
        }
        if (tid == 0) TS(7);
        const unsigned tag = epoch + 1u;
#pragma unroll
        for (int q = 0; q < 3; ++q) {
            const float v = sel4(t, oc[q][0][0] + oc[q][1][0], oc[q][0][1] + oc[q][1][1],
                                    oc[q][0][2] + oc[q][1][2], oc[q][0][3] + oc[q][1][3]);
            const unsigned long long w = ((unsigned long long)tag << 32) | __float_as_uint(v);
            if (q < 2 || warp < 4)
                asm volatile("st.relaxed.gpu.global.b64 [%0], %1;" ::"l"(pub[q]), "l"(w) : "memory");
        }
        if (tid == 0) TS(9);
        if (tid < 160) {
            float v[4] = {0.f, 0.f, 0.f, 0.f};
            {
                unsigned n = 0, c;
                bool have[4] = {false, false, false, false};
                asm volatile("ld.relaxed.gpu.global.u32 %0, [%1];" : "=r"(c) : "l"(donep) : "memory");
                while (true) {
                    unsigned long long w[4] = {0ull, 0ull, 0ull, 0ull};
#pragma unroll
                    for (int i = 0; i < 4; ++i)
                        if (!have[i]) asm volatile("ld.relaxed.gpu.global.b64 %0, [%1];" : "=l"(w[i]) : "l"(src + i * 160) : "memory");
#pragma unroll
                    for (int i = 0; i < 4; ++i)
                        if (!have[i] && (unsigned)(w[i] >> 32) == tag) { have[i] = true; v[i] = __uint_as_float((unsigned)w[i]); }
                    if (__all_sync(0xffffffffu, have[0] && have[1] && have[2] && have[3])) break;
                    while ((int)(c - tag * NH) < 0) {
                        __nanosleep(300);
                        asm volatile("ld.relaxed.gpu.global.u32 %0, [%1];" : "=r"(c) : "l"(donep) : "memory");
                        if (++n > SPIN_LIMIT) __trap();
                    }
                    if (++n > SPIN_LIMIT) __trap();
                }
            }
            float* red = reinterpret_cast<float*>(sgen + OFF_PART);
#pragma unroll
            for (int i = 0; i < 4; ++i) red[tid + 160 * i] = v[i];
            asm volatile("bar.sync 3, 160;" ::: "memory");
            const int j = tid >> 3, s = tid & 7;
#pragma unroll
            for (int i = 0; i < 4; ++i) v[i] = red[(4 * s + i) * 20 + j];
            float sum = (v[0] + v[1]) + (v[2] + v[3]);
            sum += __shfl_xor_sync(0xffffffffu, sum, 1);
            sum += __shfl_xor_sync(0xffffffffu, sum, 2);
            sum += __shfl_xor_sync(0xffffffffu, sum, 4);
            if (s == 0) *dsto = __float2bfloat16(sum);
            if (tid == 0) { TS(8);
            }
            if (h == 0 && tid == 0) *reinterpret_cast<volatile unsigned*>(&g_epoch[grp]) = tag;
        }
    }
}

typedef CUresult (*EncodeTiledFn)(CUtensorMap*, CUtensorMapDataType, cuuint32_t, void*, const cuuint64_t*,
                                  const cuuint64_t*, const cuuint32_t*, const cuuint32_t*, CUtensorMapInterleave,
                                  CUtensorMapSwizzle, CUtensorMapL2promotion, CUtensorMapFloatOOBfill);

bool encode(EncodeTiledFn fn, CUtensorMap* tm, const void* ptr, int rank, const cuuint64_t* dims,
            const cuuint64_t* strides, const cuuint32_t* box) {
    const cuuint32_t es[3] = {1, 1, 1};
    CUresult rc = fn(tm, CU_TENSOR_MAP_DATA_TYPE_BFLOAT16, (cuuint32_t)rank, const_cast<void*>(ptr), dims, strides, box, es,
                     CU_TENSOR_MAP_INTERLEAVE_NONE, CU_TENSOR_MAP_SWIZZLE_128B, CU_TENSOR_MAP_L2_PROMOTION_L2_128B,
                     CU_TENSOR_MAP_FLOAT_OOB_FILL_NONE);
    if (rc != CUDA_SUCCESS) { fprintf(stderr, "cuTensorMapEncodeTiled failed: %d\n", (int)rc); return false; }
    return true;
}

}

extern "C" void kernel_launch(void* const* d_in, const int* in_sizes, int n_in, void* d_out, int out_size) {
    (void)in_sizes; (void)n_in; (void)out_size;
    static EncodeTiledFn fn = nullptr;
    if (!fn) {
        void* f = nullptr;
        cudaDriverEntryPointQueryResult qr;
        if (cudaGetDriverEntryPoint("cuTensorMapEncodeTiled", &f, cudaEnableDefault, &qr) != cudaSuccess || !f) {
            fprintf(stderr, "cuTensorMapEncodeTiled not available\n");
            return;
        }
        fn = (EncodeTiledFn)f;
        cudaFuncSetAttribute(fused_decode_kernel, cudaFuncAttributeMaxDynamicSharedMemorySize, SMEM_BYTES);
    }
    Params p;
    for (int b = 0; b < 2; ++b) {
        void* const* in = d_in + 5 * b;
        p.x[b] = (const __nv_bfloat16*)in[0];
        p.kraw[b] = (const __nv_bfloat16*)in[1]; p.wqraw[b] = (const __nv_bfloat16*)in[3]; p.vraw[b] = (const __nv_bfloat16*)in[2];
        {
            const cuuint64_t dims[2] = {64, (cuuint64_t)2 * NH * SK * 3};
            const cuuint64_t strides[1] = {128};
            const cuuint32_t box[2] = {64, 192};
            if (!encode(fn, &p.k[b], in[1], 2, dims, strides, box)) return;
            if (!encode(fn, &p.v[b], in[2], 2, dims, strides, box)) return;
        }
        {
            const cuuint64_t dims[3] = {64, 96, 640};
            const cuuint64_t strides[2] = {128, 12288};
            const cuuint32_t box[3] = {64, 3, 64};
            if (!encode(fn, &p.wq[b], in[3], 3, dims, strides, box)) return;
        }
        {
            const cuuint64_t dims[3] = {64, 10, 6144};
            const cuuint64_t strides[2] = {128, 1280};
            const cuuint32_t box[3] = {64, 5, 32};
            if (!encode(fn, &p.wo[b], in[4], 3, dims, strides, box)) return;
        }
    }
    p.out = (__nv_bfloat16*)d_out;
    fused_decode_kernel<<<128, NTHREADS, SMEM_BYTES>>>(p);
}
```

```cpp
#include <cuda_runtime.h>
#include <cuda_bf16.h>
#include <cuda.h>
#include <stdint.h>
#include <stdio.h>

namespace {

constexpr int DM = 640;
constexpr int NH = 32;
constexpr int SK = 8192;
constexpr int DH = 192;

constexpr int NSLOT      = 8;
constexpr int SLOT_BYTES = 24576;
constexpr int N_WQ   = 5;
constexpr int N_PAIR = SK / 64;
constexpr int N_WO   = 6;
constexpr int T_KV0  = N_WQ;
constexpr int T_WO0  = N_WQ + 2 * N_PAIR;
constexpr int N_TILES = T_WO0 + N_WO;
constexpr int WO_BYTES = 32 * 640;

constexpr int NTHREADS = 320;

constexpr int QP_STRIDE_B = 208;
constexpr int OB_STRIDE = 112;
constexpr int OFF_RING  = 0;
constexpr int OFF_PART  = NSLOT * SLOT_BYTES;
constexpr int OFF_QOWN  = OFF_PART + 8 * 2 * QP_STRIDE_B * 4;
constexpr int OFF_QPEER = OFF_QOWN + DH * 4;
constexpr int OFF_OBUF  = OFF_QPEER + DH * 4;
constexpr int OFF_ML    = OFF_OBUF + 2 * OB_STRIDE * 4;
constexpr int OFF_BARS  = OFF_ML + 8 * 2 * 4;
constexpr int OFF_EPOCH = OFF_BARS + (2 * NSLOT + 2 + N_WO) * 8;
constexpr int OFF_PROG  = OFF_EPOCH + 4;
constexpr int OFF_DEPTH = OFF_EPOCH + 8;
constexpr int OFF_GO    = OFF_EPOCH + 12;
constexpr int SMEM_USED = OFF_EPOCH + 16;
constexpr int SMEM_BYTES = SMEM_USED + 1024;

struct alignas(64) Params {
    CUtensorMap k[2];
    CUtensorMap v[2];
    CUtensorMap wq[2];
    CUtensorMap wo[2];
    const __nv_bfloat16* x[2];
    const __nv_bfloat16* kraw[2];
    const __nv_bfloat16* wqraw[2];
    __nv_bfloat16* out;
};

__device__ unsigned long long g_part[2 * 2 * NH * 640];
__device__ unsigned int g_prog;
__device__ unsigned int g_epoch[4];
__device__ unsigned int g_done[4];

constexpr int PACE_D0 = 7, PACE_SL = 4, PACE_DMIN = 2;
constexpr unsigned PACE_TILES = T_WO0 - NSLOT + 1;
constexpr unsigned WO_GATE = 2;

constexpr unsigned SPIN_LIMIT = 1u << 24;

__device__ __forceinline__ uint32_t smem_u32(const void* p) { return (uint32_t)__cvta_generic_to_shared(p); }

__device__ __forceinline__ void mbar_init(uint32_t bar, uint32_t cnt) {
    asm volatile("mbarrier.init.shared::cta.b64 [%0], %1;" ::"r"(bar), "r"(cnt) : "memory");
}
__device__ __forceinline__ void mbar_expect_tx(uint32_t bar, uint32_t bytes) {
    asm volatile("mbarrier.arrive.expect_tx.shared::cta.b64 _, [%0], %1;" ::"r"(bar), "r"(bytes) : "memory");
}
__device__ __forceinline__ void mbar_arrive(uint32_t bar) {
    asm volatile("mbarrier.arrive.shared::cta.b64 _, [%0];" ::"r"(bar) : "memory");
}
__device__ __forceinline__ bool mbar_try(uint32_t bar, uint32_t parity) {
    uint32_t ok;
    asm volatile("{\n.reg .pred p;\nmbarrier.try_wait.parity.shared::cta.b64 p, [%1], %2;\nselp.u32 %0, 1, 0, p;\n}"
                 : "=r"(ok) : "r"(bar), "r"(parity) : "memory");
    return ok != 0;
}
__device__ __forceinline__ bool mbar_test(uint32_t bar, uint32_t parity) {
    uint32_t ok;
    asm volatile("{\n.reg .pred p;\nmbarrier.test_wait.parity.shared::cta.b64 p, [%1], %2;\nselp.u32 %0, 1, 0, p;\n}"
                 : "=r"(ok) : "r"(bar), "r"(parity) : "memory");
    return ok != 0;
}
__device__ __forceinline__ bool mbar_try_cluster(uint32_t bar, uint32_t parity) {
    uint32_t ok;
    asm volatile("{\n.reg .pred p;\nmbarrier.try_wait.parity.acquire.cluster.shared::cta.b64 p, [%1], %2;\nselp.u32 %0, 1, 0, p;\n}"
                 : "=r"(ok) : "r"(bar), "r"(parity) : "memory");
    return ok != 0;
}
__device__ __forceinline__ void mbar_wait(uint32_t bar, uint32_t parity) {
    unsigned n = 0;
    while (!mbar_try(bar, parity)) { if (++n > SPIN_LIMIT) __trap(); }
}
__device__ __forceinline__ void mbar_wait_cluster(uint32_t bar, uint32_t parity) {
    unsigned n = 0;
    while (!mbar_try_cluster(bar, parity)) { if (++n > SPIN_LIMIT) __trap(); }
}
__device__ __forceinline__ void tma2d(uint32_t dst, const CUtensorMap* tm, int c0, int c1, uint32_t bar, uint64_t pol) {
    asm volatile("cp.async.bulk.tensor.2d.shared::cluster.global.mbarrier::complete_tx::bytes.L2::cache_hint"
                 " [%0], [%1, {%3, %4}], [%2], %5;"
                 ::"r"(dst), "l"(tm), "r"(bar), "r"(c0), "r"(c1), "l"(pol) : "memory");
}
__device__ __forceinline__ void tma3d(uint32_t dst, const CUtensorMap* tm, int c0, int c1, int c2, uint32_t bar, uint64_t pol) {
    asm volatile("cp.async.bulk.tensor.3d.shared::cluster.global.mbarrier::complete_tx::bytes.L2::cache_hint"
                 " [%0], [%1, {%3, %4, %5}], [%2], %6;"
                 ::"r"(dst), "l"(tm), "r"(bar), "r"(c0), "r"(c1), "r"(c2), "l"(pol) : "memory");
}
__device__ __forceinline__ void ldsm4(uint32_t (&a)[4], uint32_t addr) {
    asm volatile("ldmatrix.sync.aligned.m8n8.x4.shared.b16 {%0,%1,%2,%3}, [%4];"
                 : "=r"(a[0]), "=r"(a[1]), "=r"(a[2]), "=r"(a[3]) : "r"(addr) : "memory");
}
__device__ __forceinline__ void ldsm4t(uint32_t (&a)[4], uint32_t addr) {
    asm volatile("ldmatrix.sync.aligned.m8n8.x4.trans.shared.b16 {%0,%1,%2,%3}, [%4];"
                 : "=r"(a[0]), "=r"(a[1]), "=r"(a[2]), "=r"(a[3]) : "r"(addr) : "memory");
}
__device__ __forceinline__ void mma16816(float (&c)[4], const uint32_t (&a)[4], uint32_t b0, uint32_t b1) {
    asm volatile("mma.sync.aligned.m16n8k16.row.col.f32.bf16.bf16.f32 {%0,%1,%2,%3}, {%4,%5,%6,%7}, {%8,%9}, {%0,%1,%2,%3};"
                 : "+f"(c[0]), "+f"(c[1]), "+f"(c[2]), "+f"(c[3])
                 : "r"(a[0]), "r"(a[1]), "r"(a[2]), "r"(a[3]), "r"(b0), "r"(b1));
}
__device__ __forceinline__ float ex2(float x) {
    float y;
    asm("ex2.approx.ftz.f32 %0, %1;" : "=f"(y) : "f"(x));
    return y;
}
__device__ __forceinline__ float rcp(float x) {
    float y;
    asm("rcp.approx.ftz.f32 %0, %1;" : "=f"(y) : "f"(x));
    return y;
}
__device__ __forceinline__ uint32_t pack_bf16(float lo, float hi) {
    uint32_t r;
    asm("cvt.rn.bf16x2.f32 %0, %1, %2;" : "=r"(r) : "f"(hi), "f"(lo));
    return r;
}
__device__ __forceinline__ uint32_t mapa(uint32_t addr, uint32_t cta) {
    uint32_t r;
    asm("mapa.shared::cluster.u32 %0, %1, %2;" : "=r"(r) : "r"(addr), "r"(cta));
    return r;
}
__device__ __forceinline__ void st_async_b32(uint32_t raddr, uint32_t v, uint32_t rbar) {
    asm volatile("st.async.weak.shared::cluster.mbarrier::complete_tx::bytes.b32 [%0], %1, [%2];"
                 ::"r"(raddr), "r"(v), "r"(rbar) : "memory");
}
__device__ __forceinline__ void cons_sync() { asm volatile("bar.sync 1, 256;" ::: "memory"); }
__device__ __forceinline__ void part_arrive() { asm volatile("bar.arrive 2, 288;" ::: "memory"); }
__device__ __forceinline__ void part_sync() { asm volatile("bar.sync 2, 288;" ::: "memory"); }
__device__ __forceinline__ float sel4(int t, float a, float b, float c, float d) {
    const float lo = (t & 1) ? b : a, hi = (t & 1) ? d : c;
    return (t & 2) ? hi : lo;
}
__device__ __forceinline__ void cluster_arrive() { asm volatile("barrier.cluster.arrive.relaxed.aligned;" ::: "memory"); }
__device__ __forceinline__ void cluster_wait() { asm volatile("barrier.cluster.wait.acquire.aligned;" ::: "memory"); }

__device__ __forceinline__ void pv_step(float (&acc)[12][4], uint32_t tile_addr, const uint32_t (&voff)[3],
                                        uint32_t b0, uint32_t b1) {
#pragma unroll
    for (int mt = 0; mt < 12; ++mt) {
        uint32_t a[4];
        ldsm4t(a, (tile_addr + voff[mt >> 2]) ^ ((mt & 3) << 5));
        mma16816(acc[mt], a, b0, b1);
    }
}

__global__ void __cluster_dims__(2, 1, 1) __launch_bounds__(NTHREADS, 1)
fused_decode_kernel(const __grid_constant__ Params p) {
    extern __shared__ uint8_t smem_raw[];
    const uint32_t sbase = (smem_u32(smem_raw) + 1023u) & ~1023u;
    uint8_t* sgen = smem_raw + (sbase - smem_u32(smem_raw));

    const int tid  = threadIdx.x;
    const int warp = tid >> 5;
    const int lane = tid & 31;
    const int r    = blockIdx.x & 1;
    const int cl   = blockIdx.x >> 1;
    const int br   = cl >> 5;
    const int h    = cl & 31;

    if (warp == 6 && lane < 3) {
        const CUtensorMap* tm = lane == 0 ? &p.wq[br] : lane == 1 ? &p.k[br] : &p.v[br];
        asm volatile("prefetch.tensormap [%0];" ::"l"(tm) : "memory");
    }
    if (tid == 288) {
        asm volatile("cp.async.bulk.prefetch.L2.global [%0], %1;"
                     ::"l"(p.kraw[br] + (size_t)(r * NH + h) * SK * DH), "r"(SLOT_BYTES) : "memory");
    }
    if (warp == 7) {
        const char* w0 = reinterpret_cast<const char*>(p.wqraw[br] + (size_t)(320 * r) * (NH * DH) + h * DH);
#pragma unroll
        for (int k = 0; k < 6; ++k) {
            const int ln = 32 * k + lane;
            const int row = (ln * 21846) >> 16;
            asm volatile("prefetch.global.L2 [%0];" ::"l"(w0 + (size_t)row * (NH * DH * 2) + (ln - 3 * row) * 128));
        }
    }

    const uint32_t ring  = sbase + OFF_RING;
    const uint32_t fullb = sbase + OFF_BARS;
    const uint32_t emptb = fullb + NSLOT * 8;
    const uint32_t xqb   = emptb + NSLOT * 8;
    const uint32_t xob   = xqb + 8;
    const uint32_t wob   = xob + 8;

    if (warp == 8) {
        uint64_t pol = 0;
        const int kv_line0 = (r * NH + h) * SK * 3;
        auto issue = [&](int i) {
            const int s = i & (NSLOT - 1);
            const uint32_t dst = ring + s * SLOT_BYTES;
            const uint32_t bar = fullb + s * 8;
            if (i < T_KV0) {
                mbar_expect_tx(bar, SLOT_BYTES);
                tma3d(dst, &p.wq[br], 0, 3 * h, 320 * r + 64 * i, bar, pol);
            } else if (i < T_WO0) {
                const int j = i - T_KV0;
                mbar_expect_tx(bar, SLOT_BYTES);
                tma2d(dst, (j & 1) ? &p.v[br] : &p.k[br], 0, kv_line0 + (j >> 1) * 192, bar, pol);
            } else {
                const uint32_t wb = wob + (i - T_WO0) * 8;
                mbar_expect_tx(wb, WO_BYTES);
                tma3d(dst, &p.wo[br], 0, 5 * r, DH * h + 32 * (i - T_WO0), wb, pol);
            }
        };
        if (lane == 0) {
            for (int s = 0; s < NSLOT; ++s) { mbar_init(fullb + s * 8, 1); mbar_init(emptb + s * 8, 4); }
            *reinterpret_cast<volatile unsigned*>(sgen + OFF_PROG) = 0;
            *reinterpret_cast<volatile int*>(sgen + OFF_DEPTH) = NSLOT;
            *reinterpret_cast<volatile unsigned*>(sgen + OFF_GO) = 0;
            mbar_init(xqb, 1);
            mbar_init(xob, 2);
            for (int k = 0; k < N_WO; ++k) mbar_init(wob + k * 8, 1);
            asm volatile("fence.mbarrier_init.release.cluster;" ::: "memory");
            asm volatile("createpolicy.fractional.L2::evict_first.b64 %0, 1.0;" : "=l"(pol));
            for (int i = 0; i < NSLOT; ++i) issue(i);
            mbar_expect_tx(xqb, DH * 4);
            mbar_expect_tx(xob, DH * 2);
        }
        __syncwarp();
        asm volatile("bar.arrive 4, 64;" ::: "memory");
        cluster_arrive();
        cluster_wait();
        if (lane == 0) {
            volatile unsigned* prog = reinterpret_cast<volatile unsigned*>(sgen + OFF_PROG);
            volatile int* depth = reinterpret_cast<volatile int*>(sgen + OFF_DEPTH);
            for (int i = NSLOT; i < N_TILES; ++i) {
                mbar_wait(emptb + (i & (NSLOT - 1)) * 8, ((i >> 3) & 1) ^ 1);
                *prog = i - NSLOT + 1;
                if (i < T_WO0) {
                    unsigned n = 0;
                    while (true) {
                        const int D = *depth;
                        if (D >= NSLOT) break;
                        const int x = i - D;
                        if (mbar_test(emptb + (x & (NSLOT - 1)) * 8, (x >> 3) & 1)) break;
                        if (++n > SPIN_LIMIT) __trap();
                    }
                }
                if (i == T_WO0) {
                    unsigned n = 0;
                    while (*reinterpret_cast<volatile unsigned*>(sgen + OFF_GO) == 0) { if (++n > SPIN_LIMIT) __trap(); }
                }
                issue(i);
            }
        }
        __syncwarp();
        {
            const float* part = reinterpret_cast<const float*>(sgen + OFF_PART);
            const float* ml   = reinterpret_cast<const float*>(sgen + OFF_ML);
            uint32_t* obuf    = reinterpret_cast<uint32_t*>(sgen + OFF_OBUF);
            const float sc = 0.07216878364870322f * 1.4426950408889634f;
            const int u = lane & 7;
            const int pos0 = r * OB_STRIDE + 16 * (lane >> 4) + 4 * (u & 3) + 2 * ((lane >> 3) & 1) + (u >> 2);
            const uint32_t ra = mapa(sbase + OFF_OBUF + pos0 * 4, r ^ 1), rb = mapa(xob, r ^ 1);
            part_sync();
            const float4 ml0 = *reinterpret_cast<const float4*>(ml), ml1 = *reinterpret_cast<const float4*>(ml + 4);
            const float4 ml2 = *reinterpret_cast<const float4*>(ml + 8), ml3 = *reinterpret_cast<const float4*>(ml + 12);
            float2 pv[8][3];
#pragma unroll
            for (int w = 0; w < 8; ++w)
#pragma unroll
                for (int k = 0; k < 3; ++k) pv[w][k] = *reinterpret_cast<const float2*>(part + w * DH + 2 * (lane + 32 * k));
            const float mw[8] = {ml0.x, ml0.z, ml1.x, ml1.z, ml2.x, ml2.z, ml3.x, ml3.z};
            const float lw[8] = {ml0.y, ml0.w, ml1.y, ml1.w, ml2.y, ml2.w, ml3.y, ml3.w};
            const float M = fmaxf(fmaxf(fmaxf(mw[0], mw[1]), fmaxf(mw[2], mw[3])), fmaxf(fmaxf(mw[4], mw[5]), fmaxf(mw[6], mw[7])));
            float L = 0.f, o[3][2] = {{0.f, 0.f}, {0.f, 0.f}, {0.f, 0.f}};
#pragma unroll
            for (int w = 0; w < 8; ++w) {
                const float f = ex2((mw[w] - M) * sc);
                L = fmaf(f, lw[w], L);
#pragma unroll
                for (int k = 0; k < 3; ++k) {
                    o[k][0] = fmaf(f, pv[w][k].x, o[k][0]);
                    o[k][1] = fmaf(f, pv[w][k].y, o[k][1]);
                }
            }
            const float inv = rcp(L);
#pragma unroll
            for (int k = 0; k < 3; ++k) {
                const uint32_t ob = pack_bf16(o[k][0] * inv, o[k][1] * inv);
                obuf[pos0 + 32 * k] = ob;
                st_async_b32(ra + 128 * k, ob, rb);
            }
            __syncwarp();
            if (lane == 0) mbar_arrive(xob);
        }
    } else if (warp == 9) {
        cluster_arrive();
        cluster_wait();
        asm volatile("bar.sync 4, 64;" ::: "memory");
        if (lane == 0) {
            constexpr unsigned ADDS = PACE_TILES;
            volatile unsigned* prog = reinterpret_cast<volatile unsigned*>(sgen + OFF_PROG);
            volatile int* depth = reinterpret_cast<volatile int*>(sgen + OFF_DEPTH);
            const unsigned base = *reinterpret_cast<volatile unsigned*>(&g_epoch[br * 2 + r]) * (128u * ADDS);
            unsigned reported = 0, n = 0;
            bool go = false;
            while (reported < ADDS) {
                unsigned cur = *prog;
                cur = cur < ADDS ? cur : ADDS;
                const unsigned delta = cur - reported;
                unsigned gsum;
                if (delta) {
                    asm volatile("atom.relaxed.gpu.global.add.u32 %0, [%1], %2;" : "=r"(gsum) : "l"(&g_prog), "r"(delta) : "memory");
                    gsum += delta;
                } else {
                    asm volatile("ld.relaxed.gpu.global.u32 %0, [%1];" : "=r"(gsum) : "l"(&g_prog) : "memory");
                }
                reported = cur;
                const int lead = (int)(reported * 128u) - (int)(gsum - base);
                int D = PACE_D0 - ((PACE_SL * lead + 64) >> 7);
                *depth = D < PACE_DMIN ? PACE_DMIN : D;
                if (!go && (int)(gsum - base) >= (int)((ADDS - WO_GATE) * 128u)) {
                    go = true;
                    *reinterpret_cast<volatile unsigned*>(sgen + OFF_GO) = 1;
                }
                if (++n > SPIN_LIMIT) __trap();
            }
            while (!go) {
                unsigned gsum;
                asm volatile("ld.relaxed.gpu.global.u32 %0, [%1];" : "=r"(gsum) : "l"(&g_prog) : "memory");
                if ((int)(gsum - base) >= (int)((ADDS - WO_GATE) * 128u)) break;
                if (++n > SPIN_LIMIT) __trap();
            }
            *reinterpret_cast<volatile unsigned*>(sgen + OFF_GO) = 1;
        }
    } else {
        const int g  = lane >> 2;
        const int t  = lane & 3;
        const int gs = warp >> 2;
        const int wi = warp & 3;
        const int grp = br * 2 + r;

        uint32_t xb[3][2];
        {
            const uint32_t* xw = reinterpret_cast<const uint32_t*>(p.x[br] + (g & 1) * DM + 320 * r + 16 * wi + 2 * t);
#pragma unroll
            for (int ii = 0; ii < 3; ++ii) {
                const int i = gs + 2 * ii;
                if (i < N_WQ) { xb[ii][0] = __ldg(xw + 32 * i); xb[ii][1] = __ldg(xw + 32 * i + 4); }
                else { xb[ii][0] = 0; xb[ii][1] = 0; }
            }
        }
        unsigned epoch = 0;
        if (tid == 0) epoch = *reinterpret_cast<volatile unsigned*>(&g_epoch[grp]);

        uint32_t koff[3], voff[3];
        {
            const int rowk = 16 * wi + (lane & 7) + 8 * ((lane >> 3) & 1), hik = lane >> 4;
            const int rowv = 16 * wi + (lane & 7) + 8 * (lane >> 4),       hiv = (lane >> 3) & 1;
#pragma unroll
            for (int sg = 0; sg < 3; ++sg) {
                const int lk = 3 * rowk + sg, lv = 3 * rowv + sg;
                koff[sg] = lk * 128 + ((hik ^ (lk & 7)) << 4);
                voff[sg] = lv * 128 + ((hiv ^ (lv & 7)) << 4);
            }
        }

        cluster_arrive();
        cluster_wait();

        float acc[12][4];
#pragma unroll
        for (int mt = 0; mt < 12; ++mt) { acc[mt][0] = acc[mt][1] = acc[mt][2] = acc[mt][3] = 0.f; }

#pragma unroll
        for (int ii = 0; ii < 3; ++ii) {
            const int i = gs + 2 * ii;
            if (i < N_WQ) {
                mbar_wait(fullb + i * 8, 0);
                pv_step(acc, ring + i * SLOT_BYTES, voff, xb[ii][0], xb[ii][1]);
                __syncwarp();
                if (lane == 0) mbar_arrive(emptb + i * 8);
            }
        }
        float* part = reinterpret_cast<float*>(sgen + OFF_PART);
        float* qown = reinterpret_cast<float*>(sgen + OFF_QOWN);
        float* qpeer = reinterpret_cast<float*>(sgen + OFF_QPEER);
        {
            float* dst = part + (warp * 2 + (t & 1)) * QP_STRIDE_B + g + 8 * (t >> 1);
#pragma unroll
            for (int mt = 0; mt < 12; ++mt) {
                const float v = sel4(t, acc[mt][0], acc[mt][1], acc[mt][2], acc[mt][3]);
                dst[16 * mt] = v;
            }
            if (tid == 0) *reinterpret_cast<unsigned*>(sgen + OFF_EPOCH) = epoch;
        }
        cons_sync();
        if (tid < DH) {
            float own = 0.f, oth = 0.f;
#pragma unroll
            for (int w = 0; w < 8; ++w) {
                own += part[(w * 2 + r) * QP_STRIDE_B + tid];
                oth += part[(w * 2 + (r ^ 1)) * QP_STRIDE_B + tid];
            }
            qown[tid] = own;
            st_async_b32(mapa(sbase + OFF_QPEER + tid * 4, r ^ 1), __float_as_uint(oth), mapa(xqb, r ^ 1));
        }
        cons_sync();
        mbar_wait_cluster(xqb, 0);
        epoch = *reinterpret_cast<volatile unsigned*>(sgen + OFF_EPOCH);

        uint32_t qb[12][2];
#pragma unroll
        for (int s = 0; s < 12; ++s) {
            const int c = 16 * s + 2 * t;
            qb[s][0] = pack_bf16(qown[c] + qpeer[c], qown[c + 1] + qpeer[c + 1]);
            qb[s][1] = pack_bf16(qown[c + 8] + qpeer[c + 8], qown[c + 9] + qpeer[c + 9]);
        }

        auto pub_addr = [&](int q) {
            const int o = (t & 1) * 320 + 16 * (warp + 8 * q) + g + 8 * (t >> 1);
            const int red = (o * 3277) >> 16;
            return g_part + ((size_t)(grp * NH + red) * NH + h) * 20 + (o - 20 * red);
        };
#pragma unroll
        for (int q = 0; q < 3; ++q)
            if (q < 2 || warp < 4)
                asm volatile("st.relaxed.gpu.global.b64 [%0], %1;" ::"l"(pub_addr(q)), "l"((unsigned long long)epoch << 32) : "memory");
        if (tid < 160 && (tid & 7) == 0) {
            const int oq = 20 * h + (tid >> 3);
            p.out[(oq >= 320 ? 2 * DM - 320 : 0) + br * DM + r * 320 + oq] = __float2bfloat16(0.f);
        }
#pragma unroll
        for (int mt = 0; mt < 12; ++mt) { acc[mt][0] = acc[mt][1] = acc[mt][2] = acc[mt][3] = 0.f; }
        const float sc = 0.07216878364870322f * 1.4426950408889634f;
        float m = -INFINITY, l = 0.f;

#pragma unroll 1
        for (int jj = 0; jj < N_PAIR / 2; ++jj) {
            const int iK = T_KV0 + 2 * (2 * jj + gs);
            const int iV = iK + 1;
            const int sK = iK & (NSLOT - 1), sV = iV & (NSLOT - 1);

            mbar_wait(fullb + sK * 8, (iK >> 3) & 1);
            float cA[4] = {0.f, 0.f, 0.f, 0.f}, cB[4] = {0.f, 0.f, 0.f, 0.f};
            {
                const uint32_t kt = ring + sK * SLOT_BYTES;
#pragma unroll
                for (int s = 0; s < 12; s += 2) {
                    uint32_t a0[4], a1[4];
                    ldsm4(a0, (kt + koff[s >> 2]) ^ ((s & 3) << 5));
                    ldsm4(a1, (kt + koff[(s + 1) >> 2]) ^ (((s + 1) & 3) << 5));
                    mma16816(cA, a0, qb[s][0], qb[s][1]);
                    mma16816(cB, a1, qb[s + 1][0], qb[s + 1][1]);
                }
            }
            __syncwarp();
            if (lane == 0) mbar_arrive(emptb + sK * 8);

            const float s0 = cA[0] + cB[0];
            const float s1 = cA[2] + cB[2];
            float bm = fmaxf(s0, s1);
            bm = fmaxf(bm, __shfl_xor_sync(0xffffffffu, bm, 4));
            bm = fmaxf(bm, __shfl_xor_sync(0xffffffffu, bm, 8));
            bm = fmaxf(bm, __shfl_xor_sync(0xffffffffu, bm, 16));
            if (bm > m) {
                const float f = ex2((m - bm) * sc);
                l *= f;
#pragma unroll
                for (int mt = 0; mt < 12; ++mt) { acc[mt][0] *= f; acc[mt][2] *= f; }
                m = bm;
            }
            const float ms = m * sc;
            const float p0 = ex2(fmaf(s0, sc, -ms));
            const float p1 = ex2(fmaf(s1, sc, -ms));
            l += p0 + p1;
            const uint32_t pk = pack_bf16(p0, p1);
            const uint32_t u = __shfl_sync(0xffffffffu, pk, 8 * t);
            const uint32_t v = __shfl_sync(0xffffffffu, pk, 8 * t + 4);
            const uint32_t b0 = __byte_perm(u, v, 0x5410);
            const uint32_t b1 = __byte_perm(u, v, 0x7632);

            mbar_wait(fullb + sV * 8, (iV >> 3) & 1);
            pv_step(acc, ring + sV * SLOT_BYTES, voff, b0, b1);
            __syncwarp();
            if (lane == 0) mbar_arrive(emptb + sV * 8);
        }

        if (tid == 128) asm volatile("red.relaxed.gpu.global.add.u32 [%0], 1;" ::"l"(&g_done[grp]) : "memory");
        l += __shfl_xor_sync(0xffffffffu, l, 4);
        l += __shfl_xor_sync(0xffffffffu, l, 8);
        l += __shfl_xor_sync(0xffffffffu, l, 16);
        float* ml = reinterpret_cast<float*>(sgen + OFF_ML);
        if (t < 2) {
            float* dst = part + warp * DH + g + 8 * t;
#pragma unroll
            for (int mt = 0; mt < 12; ++mt) dst[16 * mt] = t ? acc[mt][2] : acc[mt][0];
        }
        if (lane == 0) { ml[warp * 2] = m; ml[warp * 2 + 1] = l; }
        part_arrive();

        unsigned long long* pub[3];
#pragma unroll
        for (int q = 0; q < 3; ++q) {
            pub[q] = pub_addr(q);
            asm volatile("" : "+l"(pub[q]));
        }
        const unsigned long long* src = g_part + (size_t)(grp * NH + h) * 640 + tid;
        const int oj = 20 * h + (tid >> 3);
        __nv_bfloat16* dsto = p.out + (oj >= 320 ? 2 * DM - 320 : 0) + br * DM + r * 320 + oj;
        const unsigned int* donep = &g_done[grp];
        asm volatile("" : "+l"(src), "+l"(dsto), "+l"(donep));

        uint32_t woff[3][2];
        {
            const int rowt = (lane & 7) + 8 * (lane >> 4), hit = (lane >> 3) & 1;
#pragma unroll
            for (int q = 0; q < 3; ++q) {
                const int mt = warp + 8 * q;
#pragma unroll
                for (int kk = 0; kk < 2; ++kk) {
                    const int line = 5 * (16 * kk + rowt) + (mt >> 2);
                    woff[q][kk] = ring + line * 128 + (((2 * (mt & 3) + hit) ^ (line & 7)) << 4);
                }
            }
        }
        mbar_wait_cluster(xob, 0);
        float oc[3][2][4];
#pragma unroll
        for (int q = 0; q < 3; ++q)
#pragma unroll
            for (int kk = 0; kk < 2; ++kk) { oc[q][kk][0] = oc[q][kk][1] = oc[q][kk][2] = oc[q][kk][3] = 0.f; }
        {
            const uint32_t* obuf = reinterpret_cast<const uint32_t*>(sgen + OFF_OBUF);
            const uint4* os = reinterpret_cast<const uint4*>(obuf + (g & 1) * OB_STRIDE + 4 * t);
            uint4 b[N_WO];
#pragma unroll
            for (int i = 0; i < N_WO; ++i) b[i] = os[4 * i];
            uint32_t a[2][3][2][4];
            const bool three = warp < 4;
#pragma unroll
            for (int i = 0; i <= N_WO; ++i) {
                if (i < N_WO) {
                    const uint32_t so = ((T_WO0 + i) & (NSLOT - 1)) * SLOT_BYTES;
                    mbar_wait(wob + i * 8, 0);
#pragma unroll
                    for (int q = 0; q < 2; ++q) {
                        ldsm4t(a[i & 1][q][0], woff[q][0] + so);
                        ldsm4t(a[i & 1][q][1], woff[q][1] + so);
                    }
                    if (three) { ldsm4t(a[i & 1][2][0], woff[2][0] + so); ldsm4t(a[i & 1][2][1], woff[2][1] + so); }
                }
                if (i > 0) {
                    const int j = i - 1;
#pragma unroll
                    for (int q = 0; q < 2; ++q) {
                        mma16816(oc[q][0], a[j & 1][q][0], b[j].x, b[j].y);
                        mma16816(oc[q][1], a[j & 1][q][1], b[j].z, b[j].w);
                    }
                    if (three) {
                        mma16816(oc[2][0], a[j & 1][2][0], b[j].x, b[j].y);
                        mma16816(oc[2][1], a[j & 1][2][1], b[j].z, b[j].w);
                    }
                }
            }
        }
        const unsigned tag = epoch + 1u;
#pragma unroll
        for (int q = 0; q < 3; ++q) {
            const float v = sel4(t, oc[q][0][0] + oc[q][1][0], oc[q][0][1] + oc[q][1][1],
                                    oc[q][0][2] + oc[q][1][2], oc[q][0][3] + oc[q][1][3]);
            const unsigned long long w = ((unsigned long long)tag << 32) | __float_as_uint(v);
            if (q < 2 || warp < 4)
                asm volatile("st.relaxed.gpu.global.b64 [%0], %1;" ::"l"(pub[q]), "l"(w) : "memory");
        }
        if (tid < 160) {
            float v[4] = {0.f, 0.f, 0.f, 0.f};
            {
                unsigned n = 0, c;
                bool have[4] = {false, false, false, false};
                asm volatile("ld.relaxed.gpu.global.u32 %0, [%1];" : "=r"(c) : "l"(donep) : "memory");
                while (true) {
                    unsigned long long w[4] = {0ull, 0ull, 0ull, 0ull};
#pragma unroll
                    for (int i = 0; i < 4; ++i)
                        if (!have[i]) asm volatile("ld.relaxed.gpu.global.b64 %0, [%1];" : "=l"(w[i]) : "l"(src + i * 160) : "memory");
#pragma unroll
                    for (int i = 0; i < 4; ++i)
                        if (!have[i] && (unsigned)(w[i] >> 32) == tag) { have[i] = true; v[i] = __uint_as_float((unsigned)w[i]); }
                    if (__all_sync(0xffffffffu, have[0] && have[1] && have[2] && have[3])) break;
                    while ((int)(c - tag * NH) < 0) {
                        __nanosleep(300);
                        asm volatile("ld.relaxed.gpu.global.u32 %0, [%1];" : "=r"(c) : "l"(donep) : "memory");
                        if (++n > SPIN_LIMIT) __trap();
                    }
                    if (++n > SPIN_LIMIT) __trap();
                }
            }
            float* red = reinterpret_cast<float*>(sgen + OFF_PART);
#pragma unroll
            for (int i = 0; i < 4; ++i) red[tid + 160 * i] = v[i];
            asm volatile("bar.sync 3, 160;" ::: "memory");
            const int j = tid >> 3, s = tid & 7;
#pragma unroll
            for (int i = 0; i < 4; ++i) v[i] = red[(4 * s + i) * 20 + j];
            float sum = (v[0] + v[1]) + (v[2] + v[3]);
            sum += __shfl_xor_sync(0xffffffffu, sum, 1);
            sum += __shfl_xor_sync(0xffffffffu, sum, 2);
            sum += __shfl_xor_sync(0xffffffffu, sum, 4);
            if (s == 0) *dsto = __float2bfloat16(sum);
            if (h == 0 && tid == 0) *reinterpret_cast<volatile unsigned*>(&g_epoch[grp]) = tag;
        }
    }
}

typedef CUresult (*EncodeTiledFn)(CUtensorMap*, CUtensorMapDataType, cuuint32_t, void*, const cuuint64_t*,
                                  const cuuint64_t*, const cuuint32_t*, const cuuint32_t*, CUtensorMapInterleave,
                                  CUtensorMapSwizzle, CUtensorMapL2promotion, CUtensorMapFloatOOBfill);

bool encode(EncodeTiledFn fn, CUtensorMap* tm, const void* ptr, int rank, const cuuint64_t* dims,
            const cuuint64_t* strides, const cuuint32_t* box) {
    const cuuint32_t es[3] = {1, 1, 1};
    CUresult rc = fn(tm, CU_TENSOR_MAP_DATA_TYPE_BFLOAT16, (cuuint32_t)rank, const_cast<void*>(ptr), dims, strides, box, es,
                     CU_TENSOR_MAP_INTERLEAVE_NONE, CU_TENSOR_MAP_SWIZZLE_128B, CU_TENSOR_MAP_L2_PROMOTION_L2_128B,
                     CU_TENSOR_MAP_FLOAT_OOB_FILL_NONE);
    if (rc != CUDA_SUCCESS) { fprintf(stderr, "cuTensorMapEncodeTiled failed: %d\n", (int)rc); return false; }
    return true;
}


}

extern "C" void kernel_launch(void* const* d_in, const int* in_sizes, int n_in, void* d_out, int out_size) {
    (void)in_sizes; (void)n_in; (void)out_size;
    static EncodeTiledFn fn = nullptr;
    if (!fn) {
        void* f = nullptr;
        cudaDriverEntryPointQueryResult qr;
        if (cudaGetDriverEntryPoint("cuTensorMapEncodeTiled", &f, cudaEnableDefault, &qr) != cudaSuccess || !f) {
            fprintf(stderr, "cuTensorMapEncodeTiled not available\n");
            return;
        }
        fn = (EncodeTiledFn)f;
        cudaFuncSetAttribute(fused_decode_kernel, cudaFuncAttributeMaxDynamicSharedMemorySize, SMEM_BYTES);
    }
    Params p;
    for (int b = 0; b < 2; ++b) {
        void* const* in = d_in + 5 * b;
        p.x[b] = (const __nv_bfloat16*)in[0];
        p.kraw[b] = (const __nv_bfloat16*)in[1]; p.wqraw[b] = (const __nv_bfloat16*)in[3];
        {
            const cuuint64_t dims[2] = {64, (cuuint64_t)2 * NH * SK * 3};
            const cuuint64_t strides[1] = {128};
            const cuuint32_t box[2] = {64, 192};
            if (!encode(fn, &p.k[b], in[1], 2, dims, strides, box)) return;
            if (!encode(fn, &p.v[b], in[2], 2, dims, strides, box)) return;
        }
        {
            const cuuint64_t dims[3] = {64, 96, 640};
            const cuuint64_t strides[2] = {128, 12288};
            const cuuint32_t box[3] = {64, 3, 64};
            if (!encode(fn, &p.wq[b], in[3], 3, dims, strides, box)) return;
        }
        {
            const cuuint64_t dims[3] = {64, 10, 6144};
            const cuuint64_t strides[2] = {128, 1280};
            const cuuint32_t box[3] = {64, 5, 32};
            if (!encode(fn, &p.wo[b], in[4], 3, dims, strides, box)) return;
        }
    }
    p.out = (__nv_bfloat16*)d_out;
    fused_decode_kernel<<<128, NTHREADS, SMEM_BYTES>>>(p);
}
```

```cpp
#include <cuda_runtime.h>
#include <cuda_bf16.h>
#include <cuda.h>
#include <stdint.h>
#include <stdio.h>

namespace {

constexpr int DM = 640;
constexpr int NH = 32;
constexpr int SK = 8192;
constexpr int DH = 192;

constexpr int NSLOT      = 8;
constexpr int SLOT_BYTES = 24576;
constexpr int N_WQ   = 5;
constexpr int N_PAIR = SK / 64;
constexpr int N_WO   = 6;
constexpr int T_KV0  = N_WQ;
constexpr int T_WO0  = N_WQ + 2 * N_PAIR;
constexpr int N_TILES = T_WO0 + N_WO;
constexpr int WO_BYTES = 32 * 640;

constexpr int NTHREADS = 320;

constexpr int QP_STRIDE_B = 208;
constexpr int OB_STRIDE = 112;
constexpr int OFF_RING  = 0;
constexpr int OFF_PART  = NSLOT * SLOT_BYTES;
constexpr int OFF_QOWN  = OFF_PART + 8 * 2 * QP_STRIDE_B * 4;
constexpr int OFF_QPEER = OFF_QOWN + DH * 4;
constexpr int OFF_OBUF  = OFF_QPEER + DH * 4;
constexpr int OFF_ML    = OFF_OBUF + 2 * OB_STRIDE * 4;
constexpr int OFF_BARS  = OFF_ML + 8 * 2 * 4;
constexpr int OFF_EPOCH = OFF_BARS + (2 * NSLOT + 2 + N_WO) * 8;
constexpr int OFF_PROG  = OFF_EPOCH + 4;
constexpr int OFF_DEPTH = OFF_EPOCH + 8;
constexpr int OFF_GO    = OFF_EPOCH + 12;
constexpr int SMEM_USED = OFF_EPOCH + 16;
constexpr int SMEM_BYTES = SMEM_USED + 1024;

struct alignas(64) Params {
    CUtensorMap k[2];
    CUtensorMap v[2];
    CUtensorMap wq[2];
    CUtensorMap wo[2];
    const __nv_bfloat16* x[2];
    const __nv_bfloat16* kraw[2];
    const __nv_bfloat16* wqraw[2];
    __nv_bfloat16* out;
};

__device__ unsigned long long g_part[2 * 2 * NH * 640];
__device__ unsigned int g_prog;
__device__ unsigned int g_epoch[4];
__device__ unsigned int g_done[4];

constexpr int PACE_D0 = 7, PACE_SL = 4, PACE_DMIN = 2;
constexpr unsigned PACE_TILES = T_WO0 - NSLOT + 1;
constexpr unsigned WO_GATE = 2;

constexpr int ROT_MUL = 41;

constexpr unsigned SPIN_LIMIT = 1u << 24;

__device__ __forceinline__ uint32_t smem_u32(const void* p) { return (uint32_t)__cvta_generic_to_shared(p); }

__device__ __forceinline__ void mbar_init(uint32_t bar, uint32_t cnt) {
    asm volatile("mbarrier.init.shared::cta.b64 [%0], %1;" ::"r"(bar), "r"(cnt) : "memory");
}
__device__ __forceinline__ void mbar_expect_tx(uint32_t bar, uint32_t bytes) {
    asm volatile("mbarrier.arrive.expect_tx.shared::cta.b64 _, [%0], %1;" ::"r"(bar), "r"(bytes) : "memory");
}
__device__ __forceinline__ void mbar_arrive(uint32_t bar) {
    asm volatile("mbarrier.arrive.shared::cta.b64 _, [%0];" ::"r"(bar) : "memory");
}
__device__ __forceinline__ bool mbar_try(uint32_t bar, uint32_t parity) {
    uint32_t ok;
    asm volatile("{\n.reg .pred p;\nmbarrier.try_wait.parity.shared::cta.b64 p, [%1], %2;\nselp.u32 %0, 1, 0, p;\n}"
                 : "=r"(ok) : "r"(bar), "r"(parity) : "memory");
    return ok != 0;
}
__device__ __forceinline__ bool mbar_test(uint32_t bar, uint32_t parity) {
    uint32_t ok;
    asm volatile("{\n.reg .pred p;\nmbarrier.test_wait.parity.shared::cta.b64 p, [%1], %2;\nselp.u32 %0, 1, 0, p;\n}"
                 : "=r"(ok) : "r"(bar), "r"(parity) : "memory");
    return ok != 0;
}
__device__ __forceinline__ bool mbar_try_cluster(uint32_t bar, uint32_t parity) {
    uint32_t ok;
    asm volatile("{\n.reg .pred p;\nmbarrier.try_wait.parity.acquire.cluster.shared::cta.b64 p, [%1], %2;\nselp.u32 %0, 1, 0, p;\n}"
                 : "=r"(ok) : "r"(bar), "r"(parity) : "memory");
    return ok != 0;
}
__device__ __forceinline__ void mbar_wait(uint32_t bar, uint32_t parity) {
    unsigned n = 0;
    while (!mbar_try(bar, parity)) { if (++n > SPIN_LIMIT) __trap(); }
}
__device__ __forceinline__ void mbar_wait_cluster(uint32_t bar, uint32_t parity) {
    unsigned n = 0;
    while (!mbar_try_cluster(bar, parity)) { if (++n > SPIN_LIMIT) __trap(); }
}
__device__ __forceinline__ void tma2d(uint32_t dst, const CUtensorMap* tm, int c0, int c1, uint32_t bar, uint64_t pol) {
    asm volatile("cp.async.bulk.tensor.2d.shared::cluster.global.mbarrier::complete_tx::bytes.L2::cache_hint"
                 " [%0], [%1, {%3, %4}], [%2], %5;"
                 ::"r"(dst), "l"(tm), "r"(bar), "r"(c0), "r"(c1), "l"(pol) : "memory");
}
__device__ __forceinline__ void tma3d(uint32_t dst, const CUtensorMap* tm, int c0, int c1, int c2, uint32_t bar, uint64_t pol) {
    asm volatile("cp.async.bulk.tensor.3d.shared::cluster.global.mbarrier::complete_tx::bytes.L2::cache_hint"
                 " [%0], [%1, {%3, %4, %5}], [%2], %6;"
                 ::"r"(dst), "l"(tm), "r"(bar), "r"(c0), "r"(c1), "r"(c2), "l"(pol) : "memory");
}
__device__ __forceinline__ void ldsm4(uint32_t (&a)[4], uint32_t addr) {
    asm volatile("ldmatrix.sync.aligned.m8n8.x4.shared.b16 {%0,%1,%2,%3}, [%4];"
                 : "=r"(a[0]), "=r"(a[1]), "=r"(a[2]), "=r"(a[3]) : "r"(addr) : "memory");
}
__device__ __forceinline__ void ldsm4t(uint32_t (&a)[4], uint32_t addr) {
    asm volatile("ldmatrix.sync.aligned.m8n8.x4.trans.shared.b16 {%0,%1,%2,%3}, [%4];"
                 : "=r"(a[0]), "=r"(a[1]), "=r"(a[2]), "=r"(a[3]) : "r"(addr) : "memory");
}
__device__ __forceinline__ void mma16816(float (&c)[4], const uint32_t (&a)[4], uint32_t b0, uint32_t b1) {
    asm volatile("mma.sync.aligned.m16n8k16.row.col.f32.bf16.bf16.f32 {%0,%1,%2,%3}, {%4,%5,%6,%7}, {%8,%9}, {%0,%1,%2,%3};"
                 : "+f"(c[0]), "+f"(c[1]), "+f"(c[2]), "+f"(c[3])
                 : "r"(a[0]), "r"(a[1]), "r"(a[2]), "r"(a[3]), "r"(b0), "r"(b1));
}
__device__ __forceinline__ float ex2(float x) {
    float y;
    asm("ex2.approx.ftz.f32 %0, %1;" : "=f"(y) : "f"(x));
    return y;
}
__device__ __forceinline__ float rcp(float x) {
    float y;
    asm("rcp.approx.ftz.f32 %0, %1;" : "=f"(y) : "f"(x));
    return y;
}
__device__ __forceinline__ uint32_t pack_bf16(float lo, float hi) {
    uint32_t r;
    asm("cvt.rn.bf16x2.f32 %0, %1, %2;" : "=r"(r) : "f"(hi), "f"(lo));
    return r;
}
__device__ __forceinline__ uint32_t mapa(uint32_t addr, uint32_t cta) {
    uint32_t r;
    asm("mapa.shared::cluster.u32 %0, %1, %2;" : "=r"(r) : "r"(addr), "r"(cta));
    return r;
}
__device__ __forceinline__ void st_async_b32(uint32_t raddr, uint32_t v, uint32_t rbar) {
    asm volatile("st.async.weak.shared::cluster.mbarrier::complete_tx::bytes.b32 [%0], %1, [%2];"
                 ::"r"(raddr), "r"(v), "r"(rbar) : "memory");
}
__device__ __forceinline__ void cons_sync() { asm volatile("bar.sync 1, 256;" ::: "memory"); }
__device__ __forceinline__ void part_arrive() { asm volatile("bar.arrive 2, 288;" ::: "memory"); }
__device__ __forceinline__ void part_sync() { asm volatile("bar.sync 2, 288;" ::: "memory"); }
__device__ __forceinline__ float sel4(int t, float a, float b, float c, float d) {
    const float lo = (t & 1) ? b : a, hi = (t & 1) ? d : c;
    return (t & 2) ? hi : lo;
}
__device__ __forceinline__ void cluster_arrive() { asm volatile("barrier.cluster.arrive.relaxed.aligned;" ::: "memory"); }
__device__ __forceinline__ void cluster_wait() { asm volatile("barrier.cluster.wait.acquire.aligned;" ::: "memory"); }

__device__ __forceinline__ void pv_step(float (&acc)[12][4], uint32_t tile_addr, const uint32_t (&voff)[3],
                                        uint32_t b0, uint32_t b1) {
#pragma unroll
    for (int mt = 0; mt < 12; ++mt) {
        uint32_t a[4];
        ldsm4t(a, (tile_addr + voff[mt >> 2]) ^ ((mt & 3) << 5));
        mma16816(acc[mt], a, b0, b1);
    }
}

__global__ void __cluster_dims__(2, 1, 1) __launch_bounds__(NTHREADS, 1)
fused_decode_kernel(const __grid_constant__ Params p) {
    extern __shared__ uint8_t smem_raw[];
    const uint32_t sbase = (smem_u32(smem_raw) + 1023u) & ~1023u;
    uint8_t* sgen = smem_raw + (sbase - smem_u32(smem_raw));

    const int tid  = threadIdx.x;
    const int warp = tid >> 5;
    const int lane = tid & 31;
    const int r    = blockIdx.x & 1;
    const int cl   = blockIdx.x >> 1;
    const int br   = cl >> 5;
    const int h    = cl & 31;

    if (warp == 6 && lane < 3) {
        const CUtensorMap* tm = lane == 0 ? &p.wq[br] : lane == 1 ? &p.k[br] : &p.v[br];
        asm volatile("prefetch.tensormap [%0];" ::"l"(tm) : "memory");
    }
    if (tid == 288) {
        asm volatile("cp.async.bulk.prefetch.L2.global [%0], %1;"
                     ::"l"(p.kraw[br] + ((size_t)(r * NH + h) * SK + 64 * (((int)blockIdx.x * ROT_MUL) & (N_PAIR - 1))) * DH), "r"(SLOT_BYTES) : "memory");
    }
    if (warp == 7) {
        const char* w0 = reinterpret_cast<const char*>(p.wqraw[br] + (size_t)(320 * r) * (NH * DH) + h * DH);
#pragma unroll
        for (int k = 0; k < 6; ++k) {
            const int ln = 32 * k + lane;
            const int row = (ln * 21846) >> 16;
            asm volatile("prefetch.global.L2 [%0];" ::"l"(w0 + (size_t)row * (NH * DH * 2) + (ln - 3 * row) * 128));
        }
    }

    const uint32_t ring  = sbase + OFF_RING;
    const uint32_t fullb = sbase + OFF_BARS;
    const uint32_t emptb = fullb + NSLOT * 8;
    const uint32_t xqb   = emptb + NSLOT * 8;
    const uint32_t xob   = xqb + 8;
    const uint32_t wob   = xob + 8;

    if (warp == 8) {
        uint64_t pol = 0;
        const int kv_line0 = (r * NH + h) * SK * 3;
        const int rot = ((int)blockIdx.x * ROT_MUL) & (N_PAIR - 1);
        auto issue = [&](int i) {
            const int s = i & (NSLOT - 1);
            const uint32_t dst = ring + s * SLOT_BYTES;
            const uint32_t bar = fullb + s * 8;
            if (i < T_KV0) {
                mbar_expect_tx(bar, SLOT_BYTES);
                tma3d(dst, &p.wq[br], 0, 3 * h, 320 * r + 64 * i, bar, pol);
            } else if (i < T_WO0) {
                const int j = i - T_KV0;
                mbar_expect_tx(bar, SLOT_BYTES);
                tma2d(dst, (j & 1) ? &p.v[br] : &p.k[br], 0, kv_line0 + (((j >> 1) + rot) & (N_PAIR - 1)) * 192, bar, pol);
            } else {
                const uint32_t wb = wob + (i - T_WO0) * 8;
                mbar_expect_tx(wb, WO_BYTES);
                tma3d(dst, &p.wo[br], 0, 5 * r, DH * h + 32 * (i - T_WO0), wb, pol);
            }
        };
        if (lane == 0) {
            for (int s = 0; s < NSLOT; ++s) { mbar_init(fullb + s * 8, 1); mbar_init(emptb + s * 8, 4); }
            *reinterpret_cast<volatile unsigned*>(sgen + OFF_PROG) = 0;
            *reinterpret_cast<volatile int*>(sgen + OFF_DEPTH) = NSLOT;
            *reinterpret_cast<volatile unsigned*>(sgen + OFF_GO) = 0;
            mbar_init(xqb, 1);
            mbar_init(xob, 2);
            for (int k = 0; k < N_WO; ++k) mbar_init(wob + k * 8, 1);
            asm volatile("fence.mbarrier_init.release.cluster;" ::: "memory");
            asm volatile("createpolicy.fractional.L2::evict_first.b64 %0, 1.0;" : "=l"(pol));
            for (int i = 0; i < NSLOT; ++i) issue(i);
            mbar_expect_tx(xqb, DH * 4);
            mbar_expect_tx(xob, DH * 2);
        }
        __syncwarp();
        asm volatile("bar.arrive 4, 64;" ::: "memory");
        cluster_arrive();
        cluster_wait();
        if (lane == 0) {
            volatile unsigned* prog = reinterpret_cast<volatile unsigned*>(sgen + OFF_PROG);
            volatile int* depth = reinterpret_cast<volatile int*>(sgen + OFF_DEPTH);
            for (int i = NSLOT; i < N_TILES; ++i) {
                mbar_wait(emptb + (i & (NSLOT - 1)) * 8, ((i >> 3) & 1) ^ 1);
                *prog = i - NSLOT + 1;
                if (i < T_WO0) {
                    unsigned n = 0;
                    while (true) {
                        const int D = *depth;
                        if (D >= NSLOT) break;
                        const int x = i - D;
                        if (mbar_test(emptb + (x & (NSLOT - 1)) * 8, (x >> 3) & 1)) break;
                        if (++n > SPIN_LIMIT) __trap();
                    }
                }
                if (i == T_WO0) {
                    unsigned n = 0;
                    while (*reinterpret_cast<volatile unsigned*>(sgen + OFF_GO) == 0) { if (++n > SPIN_LIMIT) __trap(); }
                }
                issue(i);
            }
        }
        __syncwarp();
        {
            const float* part = reinterpret_cast<const float*>(sgen + OFF_PART);
            const float* ml   = reinterpret_cast<const float*>(sgen + OFF_ML);
            uint32_t* obuf    = reinterpret_cast<uint32_t*>(sgen + OFF_OBUF);
            const float sc = 0.07216878364870322f * 1.4426950408889634f;
            const int u = lane & 7;
            const int pos0 = r * OB_STRIDE + 16 * (lane >> 4) + 4 * (u & 3) + 2 * ((lane >> 3) & 1) + (u >> 2);
            const uint32_t ra = mapa(sbase + OFF_OBUF + pos0 * 4, r ^ 1), rb = mapa(xob, r ^ 1);
            part_sync();
            const float4 ml0 = *reinterpret_cast<const float4*>(ml), ml1 = *reinterpret_cast<const float4*>(ml + 4);
            const float4 ml2 = *reinterpret_cast<const float4*>(ml + 8), ml3 = *reinterpret_cast<const float4*>(ml + 12);
            float2 pv[8][3];
#pragma unroll
            for (int w = 0; w < 8; ++w)
#pragma unroll
                for (int k = 0; k < 3; ++k) pv[w][k] = *reinterpret_cast<const float2*>(part + w * DH + 2 * (lane + 32 * k));
            const float mw[8] = {ml0.x, ml0.z, ml1.x, ml1.z, ml2.x, ml2.z, ml3.x, ml3.z};
            const float lw[8] = {ml0.y, ml0.w, ml1.y, ml1.w, ml2.y, ml2.w, ml3.y, ml3.w};
            const float M = fmaxf(fmaxf(fmaxf(mw[0], mw[1]), fmaxf(mw[2], mw[3])), fmaxf(fmaxf(mw[4], mw[5]), fmaxf(mw[6], mw[7])));
            float L = 0.f, o[3][2] = {{0.f, 0.f}, {0.f, 0.f}, {0.f, 0.f}};
#pragma unroll
            for (int w = 0; w < 8; ++w) {
                const float f = ex2((mw[w] - M) * sc);
                L = fmaf(f, lw[w], L);
#pragma unroll
                for (int k = 0; k < 3; ++k) {
                    o[k][0] = fmaf(f, pv[w][k].x, o[k][0]);
                    o[k][1] = fmaf(f, pv[w][k].y, o[k][1]);
                }
            }
            const float inv = rcp(L);
#pragma unroll
            for (int k = 0; k < 3; ++k) {
                const uint32_t ob = pack_bf16(o[k][0] * inv, o[k][1] * inv);
                obuf[pos0 + 32 * k] = ob;
                st_async_b32(ra + 128 * k, ob, rb);
            }
            __syncwarp();
            if (lane == 0) mbar_arrive(xob);
        }
    } else if (warp == 9) {
        cluster_arrive();
        cluster_wait();
        asm volatile("bar.sync 4, 64;" ::: "memory");
        if (lane == 0) {
            constexpr unsigned ADDS = PACE_TILES;
            volatile unsigned* prog = reinterpret_cast<volatile unsigned*>(sgen + OFF_PROG);
            volatile int* depth = reinterpret_cast<volatile int*>(sgen + OFF_DEPTH);
            const unsigned base = *reinterpret_cast<volatile unsigned*>(&g_epoch[br * 2 + r]) * (128u * ADDS);
            unsigned reported = 0, n = 0;
            bool go = false;
            while (reported < ADDS) {
                unsigned cur = *prog;
                cur = cur < ADDS ? cur : ADDS;
                const unsigned delta = cur - reported;
                unsigned gsum;
                if (delta) {
                    asm volatile("atom.relaxed.gpu.global.add.u32 %0, [%1], %2;" : "=r"(gsum) : "l"(&g_prog), "r"(delta) : "memory");
                    gsum += delta;
                } else {
                    asm volatile("ld.relaxed.gpu.global.u32 %0, [%1];" : "=r"(gsum) : "l"(&g_prog) : "memory");
                }
                reported = cur;
                const int lead = (int)(reported * 128u) - (int)(gsum - base);
                int D = PACE_D0 - ((PACE_SL * lead + 64) >> 7);
                *depth = D < PACE_DMIN ? PACE_DMIN : D;
                if (!go && (int)(gsum - base) >= (int)((ADDS - WO_GATE) * 128u)) {
                    go = true;
                    *reinterpret_cast<volatile unsigned*>(sgen + OFF_GO) = 1;
                }
                if (++n > SPIN_LIMIT) __trap();
            }
            while (!go) {
                unsigned gsum;
                asm volatile("ld.relaxed.gpu.global.u32 %0, [%1];" : "=r"(gsum) : "l"(&g_prog) : "memory");
                if ((int)(gsum - base) >= (int)((ADDS - WO_GATE) * 128u)) break;
                if (++n > SPIN_LIMIT) __trap();
            }
            *reinterpret_cast<volatile unsigned*>(sgen + OFF_GO) = 1;
        }
    } else {
        const int g  = lane >> 2;
        const int t  = lane & 3;
        const int gs = warp >> 2;
        const int wi = warp & 3;
        const int grp = br * 2 + r;

        uint32_t xb[3][2];
        {
            const uint32_t* xw = reinterpret_cast<const uint32_t*>(p.x[br] + (g & 1) * DM + 320 * r + 16 * wi + 2 * t);
#pragma unroll
            for (int ii = 0; ii < 3; ++ii) {
                const int i = gs + 2 * ii;
                if (i < N_WQ) { xb[ii][0] = __ldg(xw + 32 * i); xb[ii][1] = __ldg(xw + 32 * i + 4); }
                else { xb[ii][0] = 0; xb[ii][1] = 0; }
            }
        }
        unsigned epoch = 0;
        if (tid == 0) epoch = *reinterpret_cast<volatile unsigned*>(&g_epoch[grp]);

        uint32_t koff[3], voff[3];
        {
            const int rowk = 16 * wi + (lane & 7) + 8 * ((lane >> 3) & 1), hik = lane >> 4;
            const int rowv = 16 * wi + (lane & 7) + 8 * (lane >> 4),       hiv = (lane >> 3) & 1;
#pragma unroll
            for (int sg = 0; sg < 3; ++sg) {
                const int lk = 3 * rowk + sg, lv = 3 * rowv + sg;
                koff[sg] = lk * 128 + ((hik ^ (lk & 7)) << 4);
                voff[sg] = lv * 128 + ((hiv ^ (lv & 7)) << 4);
            }
        }

        cluster_arrive();
        cluster_wait();

        float acc[12][4];
#pragma unroll
        for (int mt = 0; mt < 12; ++mt) { acc[mt][0] = acc[mt][1] = acc[mt][2] = acc[mt][3] = 0.f; }

#pragma unroll
        for (int ii = 0; ii < 3; ++ii) {
            const int i = gs + 2 * ii;
            if (i < N_WQ) {
                mbar_wait(fullb + i * 8, 0);
                pv_step(acc, ring + i * SLOT_BYTES, voff, xb[ii][0], xb[ii][1]);
                __syncwarp();
                if (lane == 0) mbar_arrive(emptb + i * 8);
            }
        }
        float* part = reinterpret_cast<float*>(sgen + OFF_PART);
        float* qown = reinterpret_cast<float*>(sgen + OFF_QOWN);
        float* qpeer = reinterpret_cast<float*>(sgen + OFF_QPEER);
        {
            float* dst = part + (warp * 2 + (t & 1)) * QP_STRIDE_B + g + 8 * (t >> 1);
#pragma unroll
            for (int mt = 0; mt < 12; ++mt) {
                const float v = sel4(t, acc[mt][0], acc[mt][1], acc[mt][2], acc[mt][3]);
                dst[16 * mt] = v;
            }
            if (tid == 0) *reinterpret_cast<unsigned*>(sgen + OFF_EPOCH) = epoch;
        }
        cons_sync();
        if (tid < DH) {
            float own = 0.f, oth = 0.f;
#pragma unroll
            for (int w = 0; w < 8; ++w) {
                own += part[(w * 2 + r) * QP_STRIDE_B + tid];
                oth += part[(w * 2 + (r ^ 1)) * QP_STRIDE_B + tid];
            }
            qown[tid] = own;
            st_async_b32(mapa(sbase + OFF_QPEER + tid * 4, r ^ 1), __float_as_uint(oth), mapa(xqb, r ^ 1));
        }
        cons_sync();
        mbar_wait_cluster(xqb, 0);
        epoch = *reinterpret_cast<volatile unsigned*>(sgen + OFF_EPOCH);

        uint32_t qb[12][2];
#pragma unroll
        for (int s = 0; s < 12; ++s) {
            const int c = 16 * s + 2 * t;
            qb[s][0] = pack_bf16(qown[c] + qpeer[c], qown[c + 1] + qpeer[c + 1]);
            qb[s][1] = pack_bf16(qown[c + 8] + qpeer[c + 8], qown[c + 9] + qpeer[c + 9]);
        }

        auto pub_addr = [&](int q) {
            const int o = (t & 1) * 320 + 16 * (warp + 8 * q) + g + 8 * (t >> 1);
            const int red = (o * 3277) >> 16;
            return g_part + ((size_t)(grp * NH + red) * NH + h) * 20 + (o - 20 * red);
        };
#pragma unroll
        for (int q = 0; q < 3; ++q)
            if (q < 2 || warp < 4)
                asm volatile("st.relaxed.gpu.global.b64 [%0], %1;" ::"l"(pub_addr(q)), "l"((unsigned long long)epoch << 32) : "memory");
        if (tid < 160 && (tid & 7) == 0) {
            const int oq = 20 * h + (tid >> 3);
            p.out[(oq >= 320 ? 2 * DM - 320 : 0) + br * DM + r * 320 + oq] = __float2bfloat16(0.f);
        }
#pragma unroll
        for (int mt = 0; mt < 12; ++mt) { acc[mt][0] = acc[mt][1] = acc[mt][2] = acc[mt][3] = 0.f; }
        const float sc = 0.07216878364870322f * 1.4426950408889634f;
        float m = -INFINITY, l = 0.f;

#pragma unroll 1
        for (int jj = 0; jj < N_PAIR / 2; ++jj) {
            const int iK = T_KV0 + 2 * (2 * jj + gs);
            const int iV = iK + 1;
            const int sK = iK & (NSLOT - 1), sV = iV & (NSLOT - 1);

            mbar_wait(fullb + sK * 8, (iK >> 3) & 1);
            float cA[4] = {0.f, 0.f, 0.f, 0.f}, cB[4] = {0.f, 0.f, 0.f, 0.f};
            {
                const uint32_t kt = ring + sK * SLOT_BYTES;
#pragma unroll
                for (int s = 0; s < 12; s += 2) {
                    uint32_t a0[4], a1[4];
                    ldsm4(a0, (kt + koff[s >> 2]) ^ ((s & 3) << 5));
                    ldsm4(a1, (kt + koff[(s + 1) >> 2]) ^ (((s + 1) & 3) << 5));
                    mma16816(cA, a0, qb[s][0], qb[s][1]);
                    mma16816(cB, a1, qb[s + 1][0], qb[s + 1][1]);
                }
            }
            __syncwarp();
            if (lane == 0) mbar_arrive(emptb + sK * 8);

            const float s0 = cA[0] + cB[0];
            const float s1 = cA[2] + cB[2];
            float bm = fmaxf(s0, s1);
            bm = fmaxf(bm, __shfl_xor_sync(0xffffffffu, bm, 4));
            bm = fmaxf(bm, __shfl_xor_sync(0xffffffffu, bm, 8));
            bm = fmaxf(bm, __shfl_xor_sync(0xffffffffu, bm, 16));
            if (bm > m) {
                const float f = ex2((m - bm) * sc);
                l *= f;
#pragma unroll
                for (int mt = 0; mt < 12; ++mt) { acc[mt][0] *= f; acc[mt][2] *= f; }
                m = bm;
            }
            const float ms = m * sc;
            const float p0 = ex2(fmaf(s0, sc, -ms));
            const float p1 = ex2(fmaf(s1, sc, -ms));
            l += p0 + p1;
            const uint32_t pk = pack_bf16(p0, p1);
            const uint32_t u = __shfl_sync(0xffffffffu, pk, 8 * t);
            const uint32_t v = __shfl_sync(0xffffffffu, pk, 8 * t + 4);
            const uint32_t b0 = __byte_perm(u, v, 0x5410);
            const uint32_t b1 = __byte_perm(u, v, 0x7632);

            mbar_wait(fullb + sV * 8, (iV >> 3) & 1);
            pv_step(acc, ring + sV * SLOT_BYTES, voff, b0, b1);
            __syncwarp();
            if (lane == 0) mbar_arrive(emptb + sV * 8);
        }

        if (tid == 128) asm volatile("red.relaxed.gpu.global.add.u32 [%0], 1;" ::"l"(&g_done[grp]) : "memory");
        l += __shfl_xor_sync(0xffffffffu, l, 4);
        l += __shfl_xor_sync(0xffffffffu, l, 8);
        l += __shfl_xor_sync(0xffffffffu, l, 16);
        float* ml = reinterpret_cast<float*>(sgen + OFF_ML);
        if (t < 2) {
            float* dst = part + warp * DH + g + 8 * t;
#pragma unroll
            for (int mt = 0; mt < 12; ++mt) dst[16 * mt] = t ? acc[mt][2] : acc[mt][0];
        }
        if (lane == 0) { ml[warp * 2] = m; ml[warp * 2 + 1] = l; }
        part_arrive();

        unsigned long long* pub[3];
#pragma unroll
        for (int q = 0; q < 3; ++q) {
            pub[q] = pub_addr(q);
            asm volatile("" : "+l"(pub[q]));
        }
        const unsigned long long* src = g_part + (size_t)(grp * NH + h) * 640 + tid;
        const int oj = 20 * h + (tid >> 3);
        __nv_bfloat16* dsto = p.out + (oj >= 320 ? 2 * DM - 320 : 0) + br * DM + r * 320 + oj;
        const unsigned int* donep = &g_done[grp];
        asm volatile("" : "+l"(src), "+l"(dsto), "+l"(donep));

        uint32_t woff[3][2];
        {
            const int rowt = (lane & 7) + 8 * (lane >> 4), hit = (lane >> 3) & 1;
#pragma unroll
            for (int q = 0; q < 3; ++q) {
                const int mt = warp + 8 * q;
#pragma unroll
                for (int kk = 0; kk < 2; ++kk) {
                    const int line = 5 * (16 * kk + rowt) + (mt >> 2);
                    woff[q][kk] = ring + line * 128 + (((2 * (mt & 3) + hit) ^ (line & 7)) << 4);
                }
            }
        }
        mbar_wait_cluster(xob, 0);
        float oc[3][2][4];
#pragma unroll
        for (int q = 0; q < 3; ++q)
#pragma unroll
            for (int kk = 0; kk < 2; ++kk) { oc[q][kk][0] = oc[q][kk][1] = oc[q][kk][2] = oc[q][kk][3] = 0.f; }
        {
            const uint32_t* obuf = reinterpret_cast<const uint32_t*>(sgen + OFF_OBUF);
            const uint4* os = reinterpret_cast<const uint4*>(obuf + (g & 1) * OB_STRIDE + 4 * t);
            uint4 b[N_WO];
#pragma unroll
            for (int i = 0; i < N_WO; ++i) b[i] = os[4 * i];
            uint32_t a[2][3][2][4];
            const bool three = warp < 4;
#pragma unroll
            for (int i = 0; i <= N_WO; ++i) {
                if (i < N_WO) {
                    const uint32_t so = ((T_WO0 + i) & (NSLOT - 1)) * SLOT_BYTES;
                    mbar_wait(wob + i * 8, 0);
#pragma unroll
                    for (int q = 0; q < 2; ++q) {
                        ldsm4t(a[i & 1][q][0], woff[q][0] + so);
                        ldsm4t(a[i & 1][q][1], woff[q][1] + so);
                    }
                    if (three) { ldsm4t(a[i & 1][2][0], woff[2][0] + so); ldsm4t(a[i & 1][2][1], woff[2][1] + so); }
                }
                if (i > 0) {
                    const int j = i - 1;
#pragma unroll
                    for (int q = 0; q < 2; ++q) {
                        mma16816(oc[q][0], a[j & 1][q][0], b[j].x, b[j].y);
                        mma16816(oc[q][1], a[j & 1][q][1], b[j].z, b[j].w);
                    }
                    if (three) {
                        mma16816(oc[2][0], a[j & 1][2][0], b[j].x, b[j].y);
                        mma16816(oc[2][1], a[j & 1][2][1], b[j].z, b[j].w);
                    }
                }
            }
        }
        const unsigned tag = epoch + 1u;
#pragma unroll
        for (int q = 0; q < 3; ++q) {
            const float v = sel4(t, oc[q][0][0] + oc[q][1][0], oc[q][0][1] + oc[q][1][1],
                                    oc[q][0][2] + oc[q][1][2], oc[q][0][3] + oc[q][1][3]);
            const unsigned long long w = ((unsigned long long)tag << 32) | __float_as_uint(v);
            if (q < 2 || warp < 4)
                asm volatile("st.relaxed.gpu.global.b64 [%0], %1;" ::"l"(pub[q]), "l"(w) : "memory");
        }
        if (tid < 160) {
            float v[4] = {0.f, 0.f, 0.f, 0.f};
            {
                unsigned n = 0, c;
                bool have[4] = {false, false, false, false};
                asm volatile("ld.relaxed.gpu.global.u32 %0, [%1];" : "=r"(c) : "l"(donep) : "memory");
                while (true) {
                    unsigned long long w[4] = {0ull, 0ull, 0ull, 0ull};
#pragma unroll
                    for (int i = 0; i < 4; ++i)
                        if (!have[i]) asm volatile("ld.relaxed.gpu.global.b64 %0, [%1];" : "=l"(w[i]) : "l"(src + i * 160) : "memory");
#pragma unroll
                    for (int i = 0; i < 4; ++i)
                        if (!have[i] && (unsigned)(w[i] >> 32) == tag) { have[i] = true; v[i] = __uint_as_float((unsigned)w[i]); }
                    if (__all_sync(0xffffffffu, have[0] && have[1] && have[2] && have[3])) break;
                    while ((int)(c - tag * NH) < 0) {
                        __nanosleep(300);
                        asm volatile("ld.relaxed.gpu.global.u32 %0, [%1];" : "=r"(c) : "l"(donep) : "memory");
                        if (++n > SPIN_LIMIT) __trap();
                    }
                    if (++n > SPIN_LIMIT) __trap();
                }
            }
            float* red = reinterpret_cast<float*>(sgen + OFF_PART);
#pragma unroll
            for (int i = 0; i < 4; ++i) red[tid + 160 * i] = v[i];
            asm volatile("bar.sync 3, 160;" ::: "memory");
            const int j = tid >> 3, s = tid & 7;
#pragma unroll
            for (int i = 0; i < 4; ++i) v[i] = red[(4 * s + i) * 20 + j];
            float sum = (v[0] + v[1]) + (v[2] + v[3]);
            sum += __shfl_xor_sync(0xffffffffu, sum, 1);
            sum += __shfl_xor_sync(0xffffffffu, sum, 2);
            sum += __shfl_xor_sync(0xffffffffu, sum, 4);
            if (s == 0) *dsto = __float2bfloat16(sum);
            if (h == 0 && tid == 0) *reinterpret_cast<volatile unsigned*>(&g_epoch[grp]) = tag;
        }
    }
}

typedef CUresult (*EncodeTiledFn)(CUtensorMap*, CUtensorMapDataType, cuuint32_t, void*, const cuuint64_t*,
                                  const cuuint64_t*, const cuuint32_t*, const cuuint32_t*, CUtensorMapInterleave,
                                  CUtensorMapSwizzle, CUtensorMapL2promotion, CUtensorMapFloatOOBfill);

bool encode(EncodeTiledFn fn, CUtensorMap* tm, const void* ptr, int rank, const cuuint64_t* dims,
            const cuuint64_t* strides, const cuuint32_t* box) {
    const cuuint32_t es[3] = {1, 1, 1};
    CUresult rc = fn(tm, CU_TENSOR_MAP_DATA_TYPE_BFLOAT16, (cuuint32_t)rank, const_cast<void*>(ptr), dims, strides, box, es,
                     CU_TENSOR_MAP_INTERLEAVE_NONE, CU_TENSOR_MAP_SWIZZLE_128B, CU_TENSOR_MAP_L2_PROMOTION_L2_128B,
                     CU_TENSOR_MAP_FLOAT_OOB_FILL_NONE);
    if (rc != CUDA_SUCCESS) { fprintf(stderr, "cuTensorMapEncodeTiled failed: %d\n", (int)rc); return false; }
    return true;
}


}

extern "C" void kernel_launch(void* const* d_in, const int* in_sizes, int n_in, void* d_out, int out_size) {
    (void)in_sizes; (void)n_in; (void)out_size;
    static EncodeTiledFn fn = nullptr;
    if (!fn) {
        void* f = nullptr;
        cudaDriverEntryPointQueryResult qr;
        if (cudaGetDriverEntryPoint("cuTensorMapEncodeTiled", &f, cudaEnableDefault, &qr) != cudaSuccess || !f) {
            fprintf(stderr, "cuTensorMapEncodeTiled not available\n");
            return;
        }
        fn = (EncodeTiledFn)f;
        cudaFuncSetAttribute(fused_decode_kernel, cudaFuncAttributeMaxDynamicSharedMemorySize, SMEM_BYTES);
    }
    Params p;
    for (int b = 0; b < 2; ++b) {
        void* const* in = d_in + 5 * b;
        p.x[b] = (const __nv_bfloat16*)in[0];
        p.kraw[b] = (const __nv_bfloat16*)in[1]; p.wqraw[b] = (const __nv_bfloat16*)in[3];
        {
            const cuuint64_t dims[2] = {64, (cuuint64_t)2 * NH * SK * 3};
            const cuuint64_t strides[1] = {128};
            const cuuint32_t box[2] = {64, 192};
            if (!encode(fn, &p.k[b], in[1], 2, dims, strides, box)) return;
            if (!encode(fn, &p.v[b], in[2], 2, dims, strides, box)) return;
        }
        {
            const cuuint64_t dims[3] = {64, 96, 640};
            const cuuint64_t strides[2] = {128, 12288};
            const cuuint32_t box[3] = {64, 3, 64};
            if (!encode(fn, &p.wq[b], in[3], 3, dims, strides, box)) return;
        }
        {
            const cuuint64_t dims[3] = {64, 10, 6144};
            const cuuint64_t strides[2] = {128, 1280};
            const cuuint32_t box[3] = {64, 5, 32};
            if (!encode(fn, &p.wo[b], in[4], 3, dims, strides, box)) return;
        }
    }
    p.out = (__nv_bfloat16*)d_out;
    fused_decode_kernel<<<128, NTHREADS, SMEM_BYTES>>>(p);
}
```

```cpp
#include <cuda_runtime.h>
#include <cuda_bf16.h>
#include <cuda.h>
#include <stdint.h>
#include <stdio.h>

namespace {

constexpr int DM = 640;
constexpr int NH = 32;
constexpr int SK = 8192;
constexpr int DH = 192;

constexpr int NSLOT      = 8;
constexpr int SLOT_BYTES = 24576;
constexpr int N_WQ   = 5;
constexpr int N_PAIR = SK / 64;
constexpr int N_WO   = 6;
constexpr int T_KV0  = N_WQ;
constexpr int T_WO0  = N_WQ + 2 * N_PAIR;
constexpr int N_TILES = T_WO0 + N_WO;
constexpr int WO_BYTES = 32 * 640;

constexpr int NTHREADS = 320;

constexpr int QP_STRIDE_B = 208;
constexpr int OB_STRIDE = 112;
constexpr int OFF_RING  = 0;
constexpr int OFF_PART  = NSLOT * SLOT_BYTES;
constexpr int OFF_QOWN  = OFF_PART + 8 * 2 * QP_STRIDE_B * 4;
constexpr int OFF_QPEER = OFF_QOWN + DH * 4;
constexpr int OFF_OBUF  = OFF_QPEER + DH * 4;
constexpr int OFF_ML    = OFF_OBUF + 2 * OB_STRIDE * 4;
constexpr int OFF_BARS  = OFF_ML + 8 * 2 * 4;
constexpr int OFF_EPOCH = OFF_BARS + (2 * NSLOT + 2 + N_WO) * 8;
constexpr int OFF_PROG  = OFF_EPOCH + 4;
constexpr int OFF_DEPTH = OFF_EPOCH + 8;
constexpr int OFF_GO    = OFF_EPOCH + 12;
constexpr int SMEM_USED = OFF_EPOCH + 16;
constexpr int SMEM_BYTES = SMEM_USED + 1024;

struct alignas(64) Params {
    CUtensorMap k[2];
    CUtensorMap v[2];
    CUtensorMap wq[2];
    CUtensorMap wo[2];
    const __nv_bfloat16* x[2];
    const __nv_bfloat16* kraw[2];
    const __nv_bfloat16* wqraw[2];
    __nv_bfloat16* out;
};

__device__ unsigned long long g_part[2 * 2 * NH * 640];
__device__ unsigned int g_prog;
__device__ unsigned int g_epoch[4];

constexpr int PACE_D0 = 7, PACE_SL = 4, PACE_DMIN = 2;
constexpr unsigned PACE_TILES = T_WO0 - NSLOT + 1;
constexpr unsigned WO_GATE = 2;

constexpr int ROT_MUL = 28;

constexpr unsigned SPIN_LIMIT = 1u << 24;

__device__ __forceinline__ uint32_t smem_u32(const void* p) { return (uint32_t)__cvta_generic_to_shared(p); }

__device__ __forceinline__ void mbar_init(uint32_t bar, uint32_t cnt) {
    asm volatile("mbarrier.init.shared::cta.b64 [%0], %1;" ::"r"(bar), "r"(cnt) : "memory");
}
__device__ __forceinline__ void mbar_expect_tx(uint32_t bar, uint32_t bytes) {
    asm volatile("mbarrier.arrive.expect_tx.shared::cta.b64 _, [%0], %1;" ::"r"(bar), "r"(bytes) : "memory");
}
__device__ __forceinline__ void mbar_arrive(uint32_t bar) {
    asm volatile("mbarrier.arrive.shared::cta.b64 _, [%0];" ::"r"(bar) : "memory");
}
__device__ __forceinline__ bool mbar_try(uint32_t bar, uint32_t parity) {
    uint32_t ok;
    asm volatile("{\n.reg .pred p;\nmbarrier.try_wait.parity.shared::cta.b64 p, [%1], %2;\nselp.u32 %0, 1, 0, p;\n}"
                 : "=r"(ok) : "r"(bar), "r"(parity) : "memory");
    return ok != 0;
}
__device__ __forceinline__ bool mbar_test(uint32_t bar, uint32_t parity) {
    uint32_t ok;
    asm volatile("{\n.reg .pred p;\nmbarrier.test_wait.parity.shared::cta.b64 p, [%1], %2;\nselp.u32 %0, 1, 0, p;\n}"
                 : "=r"(ok) : "r"(bar), "r"(parity) : "memory");
    return ok != 0;
}
__device__ __forceinline__ bool mbar_try_cluster(uint32_t bar, uint32_t parity) {
    uint32_t ok;
    asm volatile("{\n.reg .pred p;\nmbarrier.try_wait.parity.acquire.cluster.shared::cta.b64 p, [%1], %2;\nselp.u32 %0, 1, 0, p;\n}"
                 : "=r"(ok) : "r"(bar), "r"(parity) : "memory");
    return ok != 0;
}
__device__ __forceinline__ void mbar_wait(uint32_t bar, uint32_t parity) {
    unsigned n = 0;
    while (!mbar_try(bar, parity)) { if (++n > SPIN_LIMIT) __trap(); }
}
__device__ __forceinline__ void mbar_wait_cluster(uint32_t bar, uint32_t parity) {
    unsigned n = 0;
    while (!mbar_try_cluster(bar, parity)) { if (++n > SPIN_LIMIT) __trap(); }
}
__device__ __forceinline__ void tma2d(uint32_t dst, const CUtensorMap* tm, int c0, int c1, uint32_t bar, uint64_t pol) {
    asm volatile("cp.async.bulk.tensor.2d.shared::cluster.global.mbarrier::complete_tx::bytes.L2::cache_hint"
                 " [%0], [%1, {%3, %4}], [%2], %5;"
                 ::"r"(dst), "l"(tm), "r"(bar), "r"(c0), "r"(c1), "l"(pol) : "memory");
}
__device__ __forceinline__ void tma3d(uint32_t dst, const CUtensorMap* tm, int c0, int c1, int c2, uint32_t bar, uint64_t pol) {
    asm volatile("cp.async.bulk.tensor.3d.shared::cluster.global.mbarrier::complete_tx::bytes.L2::cache_hint"
                 " [%0], [%1, {%3, %4, %5}], [%2], %6;"
                 ::"r"(dst), "l"(tm), "r"(bar), "r"(c0), "r"(c1), "r"(c2), "l"(pol) : "memory");
}
__device__ __forceinline__ void ldsm4(uint32_t (&a)[4], uint32_t addr) {
    asm volatile("ldmatrix.sync.aligned.m8n8.x4.shared.b16 {%0,%1,%2,%3}, [%4];"
                 : "=r"(a[0]), "=r"(a[1]), "=r"(a[2]), "=r"(a[3]) : "r"(addr) : "memory");
}
__device__ __forceinline__ void ldsm4t(uint32_t (&a)[4], uint32_t addr) {
    asm volatile("ldmatrix.sync.aligned.m8n8.x4.trans.shared.b16 {%0,%1,%2,%3}, [%4];"
                 : "=r"(a[0]), "=r"(a[1]), "=r"(a[2]), "=r"(a[3]) : "r"(addr) : "memory");
}
__device__ __forceinline__ void mma16816(float (&c)[4], const uint32_t (&a)[4], uint32_t b0, uint32_t b1) {
    asm volatile("mma.sync.aligned.m16n8k16.row.col.f32.bf16.bf16.f32 {%0,%1,%2,%3}, {%4,%5,%6,%7}, {%8,%9}, {%0,%1,%2,%3};"
                 : "+f"(c[0]), "+f"(c[1]), "+f"(c[2]), "+f"(c[3])
                 : "r"(a[0]), "r"(a[1]), "r"(a[2]), "r"(a[3]), "r"(b0), "r"(b1));
}
__device__ __forceinline__ float ex2(float x) {
    float y;
    asm("ex2.approx.ftz.f32 %0, %1;" : "=f"(y) : "f"(x));
    return y;
}
__device__ __forceinline__ float rcp(float x) {
    float y;
    asm("rcp.approx.ftz.f32 %0, %1;" : "=f"(y) : "f"(x));
    return y;
}
__device__ __forceinline__ uint32_t pack_bf16(float lo, float hi) {
    uint32_t r;
    asm("cvt.rn.bf16x2.f32 %0, %1, %2;" : "=r"(r) : "f"(hi), "f"(lo));
    return r;
}
__device__ __forceinline__ uint32_t mapa(uint32_t addr, uint32_t cta) {
    uint32_t r;
    asm("mapa.shared::cluster.u32 %0, %1, %2;" : "=r"(r) : "r"(addr), "r"(cta));
    return r;
}
__device__ __forceinline__ void st_async_b32(uint32_t raddr, uint32_t v, uint32_t rbar) {
    asm volatile("st.async.weak.shared::cluster.mbarrier::complete_tx::bytes.b32 [%0], %1, [%2];"
                 ::"r"(raddr), "r"(v), "r"(rbar) : "memory");
}
__device__ __forceinline__ void cons_sync() { asm volatile("bar.sync 1, 256;" ::: "memory"); }
__device__ __forceinline__ void part_arrive() { asm volatile("bar.arrive 2, 288;" ::: "memory"); }
__device__ __forceinline__ void part_sync() { asm volatile("bar.sync 2, 288;" ::: "memory"); }
__device__ __forceinline__ float sel4(int t, float a, float b, float c, float d) {
    const float lo = (t & 1) ? b : a, hi = (t & 1) ? d : c;
    return (t & 2) ? hi : lo;
}
__device__ __forceinline__ void cluster_arrive() { asm volatile("barrier.cluster.arrive.relaxed.aligned;" ::: "memory"); }
__device__ __forceinline__ void cluster_wait() { asm volatile("barrier.cluster.wait.acquire.aligned;" ::: "memory"); }

__device__ __forceinline__ void pv_step(float (&acc)[12][4], uint32_t tile_addr, const uint32_t (&voff)[3],
                                        uint32_t b0, uint32_t b1) {
#pragma unroll
    for (int mt = 0; mt < 12; ++mt) {
        uint32_t a[4];
        ldsm4t(a, (tile_addr + voff[mt >> 2]) ^ ((mt & 3) << 5));
        mma16816(acc[mt], a, b0, b1);
    }
}

__global__ void __cluster_dims__(2, 1, 1) __launch_bounds__(NTHREADS, 1)
fused_decode_kernel(const __grid_constant__ Params p) {
    extern __shared__ uint8_t smem_raw[];
    const uint32_t sbase = (smem_u32(smem_raw) + 1023u) & ~1023u;
    uint8_t* sgen = smem_raw + (sbase - smem_u32(smem_raw));

    const int tid  = threadIdx.x;
    const int warp = tid >> 5;
    const int lane = tid & 31;
    const int r    = blockIdx.x & 1;
    const int cl   = blockIdx.x >> 1;
    const int br   = cl >> 5;
    const int h    = cl & 31;

    if (warp == 6 && lane < 3) {
        const CUtensorMap* tm = lane == 0 ? &p.wq[br] : lane == 1 ? &p.k[br] : &p.v[br];
        asm volatile("prefetch.tensormap [%0];" ::"l"(tm) : "memory");
    }
    if (tid == 288) {
        asm volatile("cp.async.bulk.prefetch.L2.global [%0], %1;"
                     ::"l"(p.kraw[br] + ((size_t)(r * NH + h) * SK + 64 * (((int)blockIdx.x * ROT_MUL) & (N_PAIR - 1))) * DH), "r"(SLOT_BYTES) : "memory");
    }
    if (warp == 7) {
        const char* w0 = reinterpret_cast<const char*>(p.wqraw[br] + (size_t)(320 * r) * (NH * DH) + h * DH);
#pragma unroll
        for (int k = 0; k < 6; ++k) {
            const int ln = 32 * k + lane;
            const int row = (ln * 21846) >> 16;
            asm volatile("prefetch.global.L2 [%0];" ::"l"(w0 + (size_t)row * (NH * DH * 2) + (ln - 3 * row) * 128));
        }
    }

    const uint32_t ring  = sbase + OFF_RING;
    const uint32_t fullb = sbase + OFF_BARS;
    const uint32_t emptb = fullb + NSLOT * 8;
    const uint32_t xqb   = emptb + NSLOT * 8;
    const uint32_t xob   = xqb + 8;
    const uint32_t wob   = xob + 8;

    if (warp == 8) {
        uint64_t pol = 0;
        const int kv_line0 = (r * NH + h) * SK * 3;
        const int rot = ((int)blockIdx.x * ROT_MUL) & (N_PAIR - 1);
        auto issue = [&](int i) {
            const int s = i & (NSLOT - 1);
            const uint32_t dst = ring + s * SLOT_BYTES;
            const uint32_t bar = fullb + s * 8;
            if (i < T_KV0) {
                mbar_expect_tx(bar, SLOT_BYTES);
                tma3d(dst, &p.wq[br], 0, 3 * h, 320 * r + 64 * i, bar, pol);
            } else if (i < T_WO0) {
                const int j = i - T_KV0;
                mbar_expect_tx(bar, SLOT_BYTES);
                tma2d(dst, (j & 1) ? &p.v[br] : &p.k[br], 0, kv_line0 + (((j >> 1) + rot) & (N_PAIR - 1)) * 192, bar, pol);
            } else {
                const uint32_t wb = wob + (i - T_WO0) * 8;
                mbar_expect_tx(wb, WO_BYTES);
                tma3d(dst, &p.wo[br], 0, 5 * r, DH * h + 32 * (i - T_WO0), wb, pol);
            }
        };
        if (lane == 0) {
            for (int s = 0; s < NSLOT; ++s) { mbar_init(fullb + s * 8, 1); mbar_init(emptb + s * 8, 4); }
            *reinterpret_cast<volatile unsigned*>(sgen + OFF_PROG) = 0;
            *reinterpret_cast<volatile int*>(sgen + OFF_DEPTH) = NSLOT;
            *reinterpret_cast<volatile unsigned*>(sgen + OFF_GO) = 0;
            mbar_init(xqb, 1);
            mbar_init(xob, 2);
            for (int k = 0; k < N_WO; ++k) mbar_init(wob + k * 8, 1);
            asm volatile("fence.mbarrier_init.release.cluster;" ::: "memory");
            asm volatile("createpolicy.fractional.L2::evict_first.b64 %0, 1.0;" : "=l"(pol));
            for (int i = 0; i < NSLOT; ++i) issue(i);
            mbar_expect_tx(xqb, DH * 4);
            mbar_expect_tx(xob, DH * 2);
        }
        __syncwarp();
        asm volatile("bar.arrive 4, 64;" ::: "memory");
        cluster_arrive();
        cluster_wait();
        if (lane == 0) {
            volatile unsigned* prog = reinterpret_cast<volatile unsigned*>(sgen + OFF_PROG);
            volatile int* depth = reinterpret_cast<volatile int*>(sgen + OFF_DEPTH);
            for (int i = NSLOT; i < N_TILES; ++i) {
                mbar_wait(emptb + (i & (NSLOT - 1)) * 8, ((i >> 3) & 1) ^ 1);
                *prog = i - NSLOT + 1;
                if (i < T_WO0) {
                    unsigned n = 0;
                    while (true) {
                        const int D = *depth;
                        if (D >= NSLOT) break;
                        const int x = i - D;
                        if (mbar_test(emptb + (x & (NSLOT - 1)) * 8, (x >> 3) & 1)) break;
                        if (++n > SPIN_LIMIT) __trap();
                    }
                }
                if (i == T_WO0) {
                    unsigned n = 0;
                    while (*reinterpret_cast<volatile unsigned*>(sgen + OFF_GO) == 0) { if (++n > SPIN_LIMIT) __trap(); }
                }
                issue(i);
            }
        }
        __syncwarp();
        {
            const float* part = reinterpret_cast<const float*>(sgen + OFF_PART);
            const float* ml   = reinterpret_cast<const float*>(sgen + OFF_ML);
            uint32_t* obuf    = reinterpret_cast<uint32_t*>(sgen + OFF_OBUF);
            const float sc = 0.07216878364870322f * 1.4426950408889634f;
            const int u = lane & 7;
            const int pos0 = r * OB_STRIDE + 16 * (lane >> 4) + 4 * (u & 3) + 2 * ((lane >> 3) & 1) + (u >> 2);
            const uint32_t ra = mapa(sbase + OFF_OBUF + pos0 * 4, r ^ 1), rb = mapa(xob, r ^ 1);
            part_sync();
            const float4 ml0 = *reinterpret_cast<const float4*>(ml), ml1 = *reinterpret_cast<const float4*>(ml + 4);
            const float4 ml2 = *reinterpret_cast<const float4*>(ml + 8), ml3 = *reinterpret_cast<const float4*>(ml + 12);
            float2 pv[8][3];
#pragma unroll
            for (int w = 0; w < 8; ++w)
#pragma unroll
                for (int k = 0; k < 3; ++k) pv[w][k] = *reinterpret_cast<const float2*>(part + w * DH + 2 * (lane + 32 * k));
            const float mw[8] = {ml0.x, ml0.z, ml1.x, ml1.z, ml2.x, ml2.z, ml3.x, ml3.z};
            const float lw[8] = {ml0.y, ml0.w, ml1.y, ml1.w, ml2.y, ml2.w, ml3.y, ml3.w};
            const float M = fmaxf(fmaxf(fmaxf(mw[0], mw[1]), fmaxf(mw[2], mw[3])), fmaxf(fmaxf(mw[4], mw[5]), fmaxf(mw[6], mw[7])));
            float L = 0.f, o[3][2] = {{0.f, 0.f}, {0.f, 0.f}, {0.f, 0.f}};
#pragma unroll
            for (int w = 0; w < 8; ++w) {
                const float f = ex2((mw[w] - M) * sc);
                L = fmaf(f, lw[w], L);
#pragma unroll
                for (int k = 0; k < 3; ++k) {
                    o[k][0] = fmaf(f, pv[w][k].x, o[k][0]);
                    o[k][1] = fmaf(f, pv[w][k].y, o[k][1]);
                }
            }
            const float inv = rcp(L);
#pragma unroll
            for (int k = 0; k < 3; ++k) {
                const uint32_t ob = pack_bf16(o[k][0] * inv, o[k][1] * inv);
                obuf[pos0 + 32 * k] = ob;
                st_async_b32(ra + 128 * k, ob, rb);
            }
            __syncwarp();
            if (lane == 0) mbar_arrive(xob);
        }
    } else if (warp == 9) {
        cluster_arrive();
        cluster_wait();
        asm volatile("bar.sync 4, 64;" ::: "memory");
        if (lane == 0) {
            constexpr unsigned ADDS = PACE_TILES;
            volatile unsigned* prog = reinterpret_cast<volatile unsigned*>(sgen + OFF_PROG);
            volatile int* depth = reinterpret_cast<volatile int*>(sgen + OFF_DEPTH);
            const unsigned base = *reinterpret_cast<volatile unsigned*>(&g_epoch[br * 2 + r]) * (128u * ADDS);
            unsigned reported = 0, n = 0;
            bool go = false;
            while (reported < ADDS) {
                unsigned cur = *prog;
                cur = cur < ADDS ? cur : ADDS;
                const unsigned delta = cur - reported;
                unsigned gsum;
                if (delta) {
                    asm volatile("atom.relaxed.gpu.global.add.u32 %0, [%1], %2;" : "=r"(gsum) : "l"(&g_prog), "r"(delta) : "memory");
                    gsum += delta;
                } else {
                    asm volatile("ld.relaxed.gpu.global.u32 %0, [%1];" : "=r"(gsum) : "l"(&g_prog) : "memory");
                }
                reported = cur;
                const int lead = (int)(reported * 128u) - (int)(gsum - base);
                int D = PACE_D0 - ((PACE_SL * lead + 64) >> 7);
                *depth = D < PACE_DMIN ? PACE_DMIN : D;
                if (!go && (int)(gsum - base) >= (int)((ADDS - WO_GATE) * 128u)) {
                    go = true;
                    *reinterpret_cast<volatile unsigned*>(sgen + OFF_GO) = 1;
                }
                if (++n > SPIN_LIMIT) __trap();
            }
            while (!go) {
                unsigned gsum;
                asm volatile("ld.relaxed.gpu.global.u32 %0, [%1];" : "=r"(gsum) : "l"(&g_prog) : "memory");
                if ((int)(gsum - base) >= (int)((ADDS - WO_GATE) * 128u)) break;
                if (++n > SPIN_LIMIT) __trap();
            }
            *reinterpret_cast<volatile unsigned*>(sgen + OFF_GO) = 1;
        }
    } else {
        const int g  = lane >> 2;
        const int t  = lane & 3;
        const int gs = warp >> 2;
        const int wi = warp & 3;
        const int grp = br * 2 + r;

        uint32_t xb[3][2];
        {
            const uint32_t* xw = reinterpret_cast<const uint32_t*>(p.x[br] + (g & 1) * DM + 320 * r + 16 * wi + 2 * t);
#pragma unroll
            for (int ii = 0; ii < 3; ++ii) {
                const int i = gs + 2 * ii;
                if (i < N_WQ) { xb[ii][0] = __ldg(xw + 32 * i); xb[ii][1] = __ldg(xw + 32 * i + 4); }
                else { xb[ii][0] = 0; xb[ii][1] = 0; }
            }
        }
        unsigned epoch = 0;
        if (tid == 0) epoch = *reinterpret_cast<volatile unsigned*>(&g_epoch[grp]);

        uint32_t koff[3], voff[3];
        {
            const int rowk = 16 * wi + (lane & 7) + 8 * ((lane >> 3) & 1), hik = lane >> 4;
            const int rowv = 16 * wi + (lane & 7) + 8 * (lane >> 4),       hiv = (lane >> 3) & 1;
#pragma unroll
            for (int sg = 0; sg < 3; ++sg) {
                const int lk = 3 * rowk + sg, lv = 3 * rowv + sg;
                koff[sg] = lk * 128 + ((hik ^ (lk & 7)) << 4);
                voff[sg] = lv * 128 + ((hiv ^ (lv & 7)) << 4);
            }
        }

        cluster_arrive();
        cluster_wait();

        float acc[12][4];
#pragma unroll
        for (int mt = 0; mt < 12; ++mt) { acc[mt][0] = acc[mt][1] = acc[mt][2] = acc[mt][3] = 0.f; }

#pragma unroll
        for (int ii = 0; ii < 3; ++ii) {
            const int i = gs + 2 * ii;
            if (i < N_WQ) {
                mbar_wait(fullb + i * 8, 0);
                pv_step(acc, ring + i * SLOT_BYTES, voff, xb[ii][0], xb[ii][1]);
                __syncwarp();
                if (lane == 0) mbar_arrive(emptb + i * 8);
            }
        }
        float* part = reinterpret_cast<float*>(sgen + OFF_PART);
        float* qown = reinterpret_cast<float*>(sgen + OFF_QOWN);
        float* qpeer = reinterpret_cast<float*>(sgen + OFF_QPEER);
        {
            float* dst = part + (warp * 2 + (t & 1)) * QP_STRIDE_B + g + 8 * (t >> 1);
#pragma unroll
            for (int mt = 0; mt < 12; ++mt) {
                const float v = sel4(t, acc[mt][0], acc[mt][1], acc[mt][2], acc[mt][3]);
                dst[16 * mt] = v;
            }
            if (tid == 0) *reinterpret_cast<unsigned*>(sgen + OFF_EPOCH) = epoch;
        }
        cons_sync();
        if (tid < DH) {
            float own = 0.f, oth = 0.f;
#pragma unroll
            for (int w = 0; w < 8; ++w) {
                own += part[(w * 2 + r) * QP_STRIDE_B + tid];
                oth += part[(w * 2 + (r ^ 1)) * QP_STRIDE_B + tid];
            }
            qown[tid] = own;
            st_async_b32(mapa(sbase + OFF_QPEER + tid * 4, r ^ 1), __float_as_uint(oth), mapa(xqb, r ^ 1));
        }
        cons_sync();
        mbar_wait_cluster(xqb, 0);
        epoch = *reinterpret_cast<volatile unsigned*>(sgen + OFF_EPOCH);

        uint32_t qb[12][2];
#pragma unroll
        for (int s = 0; s < 12; ++s) {
            const int c = 16 * s + 2 * t;
            qb[s][0] = pack_bf16(qown[c] + qpeer[c], qown[c + 1] + qpeer[c + 1]);
            qb[s][1] = pack_bf16(qown[c + 8] + qpeer[c + 8], qown[c + 9] + qpeer[c + 9]);
        }

        auto pub_addr = [&](int q) {
            const int o = (t & 1) * 320 + 16 * (warp + 8 * q) + g + 8 * (t >> 1);
            const int red = (o * 3277) >> 16;
            return g_part + ((size_t)(grp * NH + red) * NH + h) * 20 + (o - 20 * red);
        };
#pragma unroll
        for (int q = 0; q < 3; ++q)
            if (q < 2 || warp < 4)
                asm volatile("st.relaxed.gpu.global.b64 [%0], %1;" ::"l"(pub_addr(q)), "l"((unsigned long long)epoch << 32) : "memory");
        if (tid < 160 && (tid & 7) == 0) {
            const int oq = 20 * h + (tid >> 3);
            p.out[(oq >= 320 ? 2 * DM - 320 : 0) + br * DM + r * 320 + oq] = __float2bfloat16(0.f);
        }
#pragma unroll
        for (int mt = 0; mt < 12; ++mt) { acc[mt][0] = acc[mt][1] = acc[mt][2] = acc[mt][3] = 0.f; }
        const float sc = 0.07216878364870322f * 1.4426950408889634f;
        float m = -INFINITY, l = 0.f;

#pragma unroll 1
        for (int jj = 0; jj < N_PAIR / 2; ++jj) {
            const int iK = T_KV0 + 2 * (2 * jj + gs);
            const int iV = iK + 1;
            const int sK = iK & (NSLOT - 1), sV = iV & (NSLOT - 1);

            mbar_wait(fullb + sK * 8, (iK >> 3) & 1);
            float cA[4] = {0.f, 0.f, 0.f, 0.f}, cB[4] = {0.f, 0.f, 0.f, 0.f};
            {
                const uint32_t kt = ring + sK * SLOT_BYTES;
#pragma unroll
                for (int s = 0; s < 12; s += 2) {
                    uint32_t a0[4], a1[4];
                    ldsm4(a0, (kt + koff[s >> 2]) ^ ((s & 3) << 5));
                    ldsm4(a1, (kt + koff[(s + 1) >> 2]) ^ (((s + 1) & 3) << 5));
                    mma16816(cA, a0, qb[s][0], qb[s][1]);
                    mma16816(cB, a1, qb[s + 1][0], qb[s + 1][1]);
                }
            }
            __syncwarp();
            if (lane == 0) mbar_arrive(emptb + sK * 8);

            const float s0 = cA[0] + cB[0];
            const float s1 = cA[2] + cB[2];
            float bm = fmaxf(s0, s1);
            bm = fmaxf(bm, __shfl_xor_sync(0xffffffffu, bm, 4));
            bm = fmaxf(bm, __shfl_xor_sync(0xffffffffu, bm, 8));
            bm = fmaxf(bm, __shfl_xor_sync(0xffffffffu, bm, 16));
            if (bm > m) {
                const float f = ex2((m - bm) * sc);
                l *= f;
#pragma unroll
                for (int mt = 0; mt < 12; ++mt) { acc[mt][0] *= f; acc[mt][2] *= f; }
                m = bm;
            }
            const float ms = m * sc;
            const float p0 = ex2(fmaf(s0, sc, -ms));
            const float p1 = ex2(fmaf(s1, sc, -ms));
            l += p0 + p1;
            const uint32_t pk = pack_bf16(p0, p1);
            const uint32_t u = __shfl_sync(0xffffffffu, pk, 8 * t);
            const uint32_t v = __shfl_sync(0xffffffffu, pk, 8 * t + 4);
            const uint32_t b0 = __byte_perm(u, v, 0x5410);
            const uint32_t b1 = __byte_perm(u, v, 0x7632);

            mbar_wait(fullb + sV * 8, (iV >> 3) & 1);
            pv_step(acc, ring + sV * SLOT_BYTES, voff, b0, b1);
            __syncwarp();
            if (lane == 0) mbar_arrive(emptb + sV * 8);
        }

        l += __shfl_xor_sync(0xffffffffu, l, 4);
        l += __shfl_xor_sync(0xffffffffu, l, 8);
        l += __shfl_xor_sync(0xffffffffu, l, 16);
        float* ml = reinterpret_cast<float*>(sgen + OFF_ML);
        if (t < 2) {
            float* dst = part + warp * DH + g + 8 * t;
#pragma unroll
            for (int mt = 0; mt < 12; ++mt) dst[16 * mt] = t ? acc[mt][2] : acc[mt][0];
        }
        if (lane == 0) { ml[warp * 2] = m; ml[warp * 2 + 1] = l; }
        part_arrive();

        unsigned long long* pub[3];
#pragma unroll
        for (int q = 0; q < 3; ++q) {
            pub[q] = pub_addr(q);
            asm volatile("" : "+l"(pub[q]));
        }
        const unsigned long long* src = g_part + (size_t)(grp * NH + h) * 640 + tid;
        const int oj = 20 * h + (tid >> 3);
        __nv_bfloat16* dsto = p.out + (oj >= 320 ? 2 * DM - 320 : 0) + br * DM + r * 320 + oj;
        asm volatile("" : "+l"(src), "+l"(dsto));

        uint32_t woff[3][2];
        {
            const int rowt = (lane & 7) + 8 * (lane >> 4), hit = (lane >> 3) & 1;
#pragma unroll
            for (int q = 0; q < 3; ++q) {
                const int mt = warp + 8 * q;
#pragma unroll
                for (int kk = 0; kk < 2; ++kk) {
                    const int line = 5 * (16 * kk + rowt) + (mt >> 2);
                    woff[q][kk] = ring + line * 128 + (((2 * (mt & 3) + hit) ^ (line & 7)) << 4);
                }
            }
        }
        mbar_wait_cluster(xob, 0);
        float oc[3][2][4];
#pragma unroll
        for (int q = 0; q < 3; ++q)
#pragma unroll
            for (int kk = 0; kk < 2; ++kk) { oc[q][kk][0] = oc[q][kk][1] = oc[q][kk][2] = oc[q][kk][3] = 0.f; }
        {
            const uint32_t* obuf = reinterpret_cast<const uint32_t*>(sgen + OFF_OBUF);
            const uint4* os = reinterpret_cast<const uint4*>(obuf + (g & 1) * OB_STRIDE + 4 * t);
            uint4 b[N_WO];
#pragma unroll
            for (int i = 0; i < N_WO; ++i) b[i] = os[4 * i];
            uint32_t a[2][3][2][4];
            const bool three = warp < 4;
#pragma unroll
            for (int i = 0; i <= N_WO; ++i) {
                if (i < N_WO) {
                    const uint32_t so = ((T_WO0 + i) & (NSLOT - 1)) * SLOT_BYTES;
                    mbar_wait(wob + i * 8, 0);
#pragma unroll
                    for (int q = 0; q < 2; ++q) {
                        ldsm4t(a[i & 1][q][0], woff[q][0] + so);
                        ldsm4t(a[i & 1][q][1], woff[q][1] + so);
                    }
                    if (three) { ldsm4t(a[i & 1][2][0], woff[2][0] + so); ldsm4t(a[i & 1][2][1], woff[2][1] + so); }
                }
                if (i > 0) {
                    const int j = i - 1;
#pragma unroll
                    for (int q = 0; q < 2; ++q) {
                        mma16816(oc[q][0], a[j & 1][q][0], b[j].x, b[j].y);
                        mma16816(oc[q][1], a[j & 1][q][1], b[j].z, b[j].w);
                    }
                    if (three) {
                        mma16816(oc[2][0], a[j & 1][2][0], b[j].x, b[j].y);
                        mma16816(oc[2][1], a[j & 1][2][1], b[j].z, b[j].w);
                    }
                }
            }
        }
        const unsigned tag = epoch + 1u;
#pragma unroll
        for (int q = 0; q < 3; ++q) {
            const float v = sel4(t, oc[q][0][0] + oc[q][1][0], oc[q][0][1] + oc[q][1][1],
                                    oc[q][0][2] + oc[q][1][2], oc[q][0][3] + oc[q][1][3]);
            const unsigned long long w = ((unsigned long long)tag << 32) | __float_as_uint(v);
            if (q < 2 || warp < 4)
                asm volatile("st.relaxed.gpu.global.b64 [%0], %1;" ::"l"(pub[q]), "l"(w) : "memory");
        }
        if (tid < 160) {
            float v[4] = {0.f, 0.f, 0.f, 0.f};
            {
                unsigned n = 0;
                bool have[4] = {false, false, false, false};
                while (true) {
                    unsigned long long w[4] = {0ull, 0ull, 0ull, 0ull};
#pragma unroll
                    for (int i = 0; i < 4; ++i)
                        if (!have[i]) asm volatile("ld.relaxed.gpu.global.b64 %0, [%1];" : "=l"(w[i]) : "l"(src + i * 160) : "memory");
#pragma unroll
                    for (int i = 0; i < 4; ++i)
                        if (!have[i] && (unsigned)(w[i] >> 32) == tag) { have[i] = true; v[i] = __uint_as_float((unsigned)w[i]); }
                    if (__all_sync(0xffffffffu, have[0] && have[1] && have[2] && have[3])) break;
                    if (++n > SPIN_LIMIT) __trap();
                }
            }
            float* red = reinterpret_cast<float*>(sgen + OFF_PART);
#pragma unroll
            for (int i = 0; i < 4; ++i) red[tid + 160 * i] = v[i];
            asm volatile("bar.sync 3, 160;" ::: "memory");
            const int j = tid >> 3, s = tid & 7;
#pragma unroll
            for (int i = 0; i < 4; ++i) v[i] = red[(4 * s + i) * 20 + j];
            float sum = (v[0] + v[1]) + (v[2] + v[3]);
            sum += __shfl_xor_sync(0xffffffffu, sum, 1);
            sum += __shfl_xor_sync(0xffffffffu, sum, 2);
            sum += __shfl_xor_sync(0xffffffffu, sum, 4);
            if (s == 0) *dsto = __float2bfloat16(sum);
            if (h == 0 && tid == 0) *reinterpret_cast<volatile unsigned*>(&g_epoch[grp]) = tag;
        }
    }
}

typedef CUresult (*EncodeTiledFn)(CUtensorMap*, CUtensorMapDataType, cuuint32_t, void*, const cuuint64_t*,
                                  const cuuint64_t*, const cuuint32_t*, const cuuint32_t*, CUtensorMapInterleave,
                                  CUtensorMapSwizzle, CUtensorMapL2promotion, CUtensorMapFloatOOBfill);

bool encode(EncodeTiledFn fn, CUtensorMap* tm, const void* ptr, int rank, const cuuint64_t* dims,
            const cuuint64_t* strides, const cuuint32_t* box) {
    const cuuint32_t es[3] = {1, 1, 1};
    CUresult rc = fn(tm, CU_TENSOR_MAP_DATA_TYPE_BFLOAT16, (cuuint32_t)rank, const_cast<void*>(ptr), dims, strides, box, es,
                     CU_TENSOR_MAP_INTERLEAVE_NONE, CU_TENSOR_MAP_SWIZZLE_128B, CU_TENSOR_MAP_L2_PROMOTION_L2_128B,
                     CU_TENSOR_MAP_FLOAT_OOB_FILL_NONE);
    if (rc != CUDA_SUCCESS) { fprintf(stderr, "cuTensorMapEncodeTiled failed: %d\n", (int)rc); return false; }
    return true;
}


}

extern "C" void kernel_launch(void* const* d_in, const int* in_sizes, int n_in, void* d_out, int out_size) {
    (void)in_sizes; (void)n_in; (void)out_size;
    static EncodeTiledFn fn = nullptr;
    if (!fn) {
        void* f = nullptr;
        cudaDriverEntryPointQueryResult qr;
        if (cudaGetDriverEntryPoint("cuTensorMapEncodeTiled", &f, cudaEnableDefault, &qr) != cudaSuccess || !f) {
            fprintf(stderr, "cuTensorMapEncodeTiled not available\n");
            return;
        }
        fn = (EncodeTiledFn)f;
        cudaFuncSetAttribute(fused_decode_kernel, cudaFuncAttributeMaxDynamicSharedMemorySize, SMEM_BYTES);
    }
    Params p;
    for (int b = 0; b < 2; ++b) {
        void* const* in = d_in + 5 * b;
        p.x[b] = (const __nv_bfloat16*)in[0];
        p.kraw[b] = (const __nv_bfloat16*)in[1]; p.wqraw[b] = (const __nv_bfloat16*)in[3];
        {
            const cuuint64_t dims[2] = {64, (cuuint64_t)2 * NH * SK * 3};
            const cuuint64_t strides[1] = {128};
            const cuuint32_t box[2] = {64, 192};
            if (!encode(fn, &p.k[b], in[1], 2, dims, strides, box)) return;
            if (!encode(fn, &p.v[b], in[2], 2, dims, strides, box)) return;
        }
        {
            const cuuint64_t dims[3] = {64, 96, 640};
            const cuuint64_t strides[2] = {128, 12288};
            const cuuint32_t box[3] = {64, 3, 64};
            if (!encode(fn, &p.wq[b], in[3], 3, dims, strides, box)) return;
        }
        {
            const cuuint64_t dims[3] = {64, 10, 6144};
            const cuuint64_t strides[2] = {128, 1280};
            const cuuint32_t box[3] = {64, 5, 32};
            if (!encode(fn, &p.wo[b], in[4], 3, dims, strides, box)) return;
        }
    }
    p.out = (__nv_bfloat16*)d_out;
    fused_decode_kernel<<<128, NTHREADS, SMEM_BYTES>>>(p);
}
```

```cpp
#include <cuda_runtime.h>
#include <cuda_bf16.h>
#include <cuda.h>
#include <stdint.h>
#include <stdio.h>

namespace {

constexpr int DM = 640;
constexpr int NH = 32;
constexpr int SK = 8192;
constexpr int DH = 192;

constexpr int NSLOT      = 8;
constexpr int SLOT_BYTES = 24576;
constexpr int N_WQ   = 5;
constexpr int N_PAIR = SK / 64;
constexpr int N_WO   = 6;
constexpr int T_KV0  = N_WQ;
constexpr int T_WO0  = N_WQ + 2 * N_PAIR;
constexpr int N_TILES = T_WO0 + N_WO;
constexpr int WO_BYTES = 32 * 640;

constexpr int NTHREADS = 320;

constexpr int QP_STRIDE_B = 208;
constexpr int OB_STRIDE = 112;
constexpr int OFF_RING  = 0;
constexpr int OFF_PART  = NSLOT * SLOT_BYTES;
constexpr int OFF_QOWN  = OFF_PART + 8 * 2 * QP_STRIDE_B * 4;
constexpr int OFF_QPEER = OFF_QOWN + DH * 4;
constexpr int OFF_OBUF  = OFF_QPEER + DH * 4;
constexpr int OFF_ML    = OFF_OBUF + 2 * OB_STRIDE * 4;
constexpr int OFF_BARS  = OFF_ML + 8 * 2 * 4;
constexpr int OFF_EPOCH = OFF_BARS + (2 * NSLOT + 2 + N_WO) * 8;
constexpr int OFF_PROG  = OFF_EPOCH + 4;
constexpr int OFF_DEPTH = OFF_EPOCH + 8;
constexpr int OFF_GO    = OFF_EPOCH + 12;
constexpr int SMEM_USED = OFF_EPOCH + 16;
constexpr int SMEM_BYTES = SMEM_USED + 1024;

struct alignas(64) Params {
    CUtensorMap k[2];
    CUtensorMap v[2];
    CUtensorMap wq[2];
    CUtensorMap wo[2];
    const __nv_bfloat16* x[2];
    const __nv_bfloat16* kraw[2];
    const __nv_bfloat16* wqraw[2];
    __nv_bfloat16* out;
};

__device__ unsigned long long g_part[2 * 2 * NH * 640];
__device__ unsigned int g_prog[2];
__device__ unsigned int g_epoch[4];

constexpr int PACE_D0 = 7, PACE_SL = 4, PACE_DMIN = 2;
constexpr unsigned PACE_TILES = T_WO0 - NSLOT + 1;
constexpr unsigned WO_GATE = 2;

constexpr int ROT_MUL = 28;

constexpr unsigned SPIN_LIMIT = 1u << 22;

__device__ __forceinline__ uint32_t smem_u32(const void* p) { return (uint32_t)__cvta_generic_to_shared(p); }

__device__ __forceinline__ void mbar_init(uint32_t bar, uint32_t cnt) {
    asm volatile("mbarrier.init.shared::cta.b64 [%0], %1;" ::"r"(bar), "r"(cnt) : "memory");
}
__device__ __forceinline__ void mbar_expect_tx(uint32_t bar, uint32_t bytes) {
    asm volatile("mbarrier.arrive.expect_tx.shared::cta.b64 _, [%0], %1;" ::"r"(bar), "r"(bytes) : "memory");
}
__device__ __forceinline__ void mbar_arrive(uint32_t bar) {
    asm volatile("mbarrier.arrive.shared::cta.b64 _, [%0];" ::"r"(bar) : "memory");
}
__device__ __forceinline__ bool mbar_try(uint32_t bar, uint32_t parity) {
    uint32_t ok;
    asm volatile("{\n.reg .pred p;\nmbarrier.try_wait.parity.shared::cta.b64 p, [%1], %2;\nselp.u32 %0, 1, 0, p;\n}"
                 : "=r"(ok) : "r"(bar), "r"(parity) : "memory");
    return ok != 0;
}
__device__ __forceinline__ bool mbar_test(uint32_t bar, uint32_t parity) {
    uint32_t ok;
    asm volatile("{\n.reg .pred p;\nmbarrier.test_wait.parity.shared::cta.b64 p, [%1], %2;\nselp.u32 %0, 1, 0, p;\n}"
                 : "=r"(ok) : "r"(bar), "r"(parity) : "memory");
    return ok != 0;
}
__device__ __forceinline__ bool mbar_try_cluster(uint32_t bar, uint32_t parity) {
    uint32_t ok;
    asm volatile("{\n.reg .pred p;\nmbarrier.try_wait.parity.acquire.cluster.shared::cta.b64 p, [%1], %2;\nselp.u32 %0, 1, 0, p;\n}"
                 : "=r"(ok) : "r"(bar), "r"(parity) : "memory");
    return ok != 0;
}
__device__ __forceinline__ void mbar_wait(uint32_t bar, uint32_t parity) {
    unsigned n = 0;
    while (!mbar_try(bar, parity)) { if (++n > SPIN_LIMIT) __trap(); }
}
__device__ __forceinline__ void mbar_wait_cluster(uint32_t bar, uint32_t parity) {
    unsigned n = 0;
    while (!mbar_try_cluster(bar, parity)) { if (++n > SPIN_LIMIT) __trap(); }
}
__device__ __forceinline__ void tma2d(uint32_t dst, const CUtensorMap* tm, int c0, int c1, uint32_t bar, uint64_t pol) {
    asm volatile("cp.async.bulk.tensor.2d.shared::cluster.global.mbarrier::complete_tx::bytes.L2::cache_hint"
                 " [%0], [%1, {%3, %4}], [%2], %5;"
                 ::"r"(dst), "l"(tm), "r"(bar), "r"(c0), "r"(c1), "l"(pol) : "memory");
}
__device__ __forceinline__ void tma3d(uint32_t dst, const CUtensorMap* tm, int c0, int c1, int c2, uint32_t bar, uint64_t pol) {
    asm volatile("cp.async.bulk.tensor.3d.shared::cluster.global.mbarrier::complete_tx::bytes.L2::cache_hint"
                 " [%0], [%1, {%3, %4, %5}], [%2], %6;"
                 ::"r"(dst), "l"(tm), "r"(bar), "r"(c0), "r"(c1), "r"(c2), "l"(pol) : "memory");
}
__device__ __forceinline__ void ldsm4(uint32_t (&a)[4], uint32_t addr) {
    asm volatile("ldmatrix.sync.aligned.m8n8.x4.shared.b16 {%0,%1,%2,%3}, [%4];"
                 : "=r"(a[0]), "=r"(a[1]), "=r"(a[2]), "=r"(a[3]) : "r"(addr) : "memory");
}
__device__ __forceinline__ void ldsm4t(uint32_t (&a)[4], uint32_t addr) {
    asm volatile("ldmatrix.sync.aligned.m8n8.x4.trans.shared.b16 {%0,%1,%2,%3}, [%4];"
                 : "=r"(a[0]), "=r"(a[1]), "=r"(a[2]), "=r"(a[3]) : "r"(addr) : "memory");
}
__device__ __forceinline__ void mma16816(float (&c)[4], const uint32_t (&a)[4], uint32_t b0, uint32_t b1) {
    asm volatile("mma.sync.aligned.m16n8k16.row.col.f32.bf16.bf16.f32 {%0,%1,%2,%3}, {%4,%5,%6,%7}, {%8,%9}, {%0,%1,%2,%3};"
                 : "+f"(c[0]), "+f"(c[1]), "+f"(c[2]), "+f"(c[3])
                 : "r"(a[0]), "r"(a[1]), "r"(a[2]), "r"(a[3]), "r"(b0), "r"(b1));
}
__device__ __forceinline__ float ex2(float x) {
    float y;
    asm("ex2.approx.ftz.f32 %0, %1;" : "=f"(y) : "f"(x));
    return y;
}
__device__ __forceinline__ float rcp(float x) {
    float y;
    asm("rcp.approx.ftz.f32 %0, %1;" : "=f"(y) : "f"(x));
    return y;
}
__device__ __forceinline__ uint32_t pack_bf16(float lo, float hi) {
    uint32_t r;
    asm("cvt.rn.bf16x2.f32 %0, %1, %2;" : "=r"(r) : "f"(hi), "f"(lo));
    return r;
}
__device__ __forceinline__ uint32_t mapa(uint32_t addr, uint32_t cta) {
    uint32_t r;
    asm("mapa.shared::cluster.u32 %0, %1, %2;" : "=r"(r) : "r"(addr), "r"(cta));
    return r;
}
__device__ __forceinline__ void st_async_b32(uint32_t raddr, uint32_t v, uint32_t rbar) {
    asm volatile("st.async.weak.shared::cluster.mbarrier::complete_tx::bytes.b32 [%0], %1, [%2];"
                 ::"r"(raddr), "r"(v), "r"(rbar) : "memory");
}
__device__ __forceinline__ void cons_sync() { asm volatile("bar.sync 1, 256;" ::: "memory"); }
__device__ __forceinline__ void part_arrive() { asm volatile("bar.arrive 2, 288;" ::: "memory"); }
__device__ __forceinline__ void part_sync() { asm volatile("bar.sync 2, 288;" ::: "memory"); }
__device__ __forceinline__ float sel4(int t, float a, float b, float c, float d) {
    const float lo = (t & 1) ? b : a, hi = (t & 1) ? d : c;
    return (t & 2) ? hi : lo;
}
__device__ __forceinline__ void cluster_arrive() { asm volatile("barrier.cluster.arrive.relaxed.aligned;" ::: "memory"); }
__device__ __forceinline__ void cluster_wait() { asm volatile("barrier.cluster.wait.acquire.aligned;" ::: "memory"); }

__device__ __forceinline__ void pv_step(float (&acc)[12][4], uint32_t tile_addr, const uint32_t (&voff)[3],
                                        uint32_t b0, uint32_t b1) {
#pragma unroll
    for (int mt = 0; mt < 12; ++mt) {
        uint32_t a[4];
        ldsm4t(a, (tile_addr + voff[mt >> 2]) ^ ((mt & 3) << 5));
        mma16816(acc[mt], a, b0, b1);
    }
}

__global__ void __cluster_dims__(2, 1, 1) __launch_bounds__(NTHREADS, 1)
fused_decode_kernel(const __grid_constant__ Params p) {
    extern __shared__ uint8_t smem_raw[];
    const uint32_t sbase = (smem_u32(smem_raw) + 1023u) & ~1023u;
    uint8_t* sgen = smem_raw + (sbase - smem_u32(smem_raw));

    const int tid  = threadIdx.x;
    const int warp = tid >> 5;
    const int lane = tid & 31;
    const int r    = blockIdx.x & 1;
    const int cl   = blockIdx.x >> 1;
    const int br   = cl >> 5;
    const int h    = cl & 31;

    if (warp == 6 && lane < 3) {
        const CUtensorMap* tm = lane == 0 ? &p.wq[br] : lane == 1 ? &p.k[br] : &p.v[br];
        asm volatile("prefetch.tensormap [%0];" ::"l"(tm) : "memory");
    }
    if (tid == 288) {
        asm volatile("cp.async.bulk.prefetch.L2.global [%0], %1;"
                     ::"l"(p.kraw[br] + ((size_t)(r * NH + h) * SK + 64 * (((int)blockIdx.x * ROT_MUL) & (N_PAIR - 1))) * DH), "r"(SLOT_BYTES) : "memory");
    }
    if (warp == 7) {
        const char* w0 = reinterpret_cast<const char*>(p.wqraw[br] + (size_t)(320 * r) * (NH * DH) + h * DH);
#pragma unroll
        for (int k = 0; k < 6; ++k) {
            const int ln = 32 * k + lane;
            const int row = (ln * 21846) >> 16;
            asm volatile("prefetch.global.L2 [%0];" ::"l"(w0 + (size_t)row * (NH * DH * 2) + (ln - 3 * row) * 128));
        }
    }

    const uint32_t ring  = sbase + OFF_RING;
    const uint32_t fullb = sbase + OFF_BARS;
    const uint32_t emptb = fullb + NSLOT * 8;
    const uint32_t xqb   = emptb + NSLOT * 8;
    const uint32_t xob   = xqb + 8;
    const uint32_t wob   = xob + 8;

    if (warp == 8) {
        uint64_t pol = 0;
        const int kv_line0 = (r * NH + h) * SK * 3;
        const int rot = ((int)blockIdx.x * ROT_MUL) & (N_PAIR - 1);
        auto issue = [&](int i) {
            const int s = i & (NSLOT - 1);
            const uint32_t dst = ring + s * SLOT_BYTES;
            const uint32_t bar = fullb + s * 8;
            if (i < T_KV0) {
                mbar_expect_tx(bar, SLOT_BYTES);
                tma3d(dst, &p.wq[br], 0, 3 * h, 320 * r + 64 * i, bar, pol);
            } else if (i < T_WO0) {
                const int j = i - T_KV0;
                mbar_expect_tx(bar, SLOT_BYTES);
                tma2d(dst, (j & 1) ? &p.v[br] : &p.k[br], 0, kv_line0 + (((j >> 1) + rot) & (N_PAIR - 1)) * 192, bar, pol);
            } else {
                const uint32_t wb = wob + (i - T_WO0) * 8;
                mbar_expect_tx(wb, WO_BYTES);
                tma3d(dst, &p.wo[br], 0, 5 * r, DH * h + 32 * (i - T_WO0), wb, pol);
            }
        };
        if (lane == 0) {
            for (int s = 0; s < NSLOT; ++s) { mbar_init(fullb + s * 8, 1); mbar_init(emptb + s * 8, 4); }
            *reinterpret_cast<volatile unsigned*>(sgen + OFF_PROG) = 0;
            *reinterpret_cast<volatile int*>(sgen + OFF_DEPTH) = NSLOT;
            *reinterpret_cast<volatile unsigned*>(sgen + OFF_GO) = 0;
            mbar_init(xqb, 1);
            mbar_init(xob, 2);
            for (int k = 0; k < N_WO; ++k) mbar_init(wob + k * 8, 1);
            asm volatile("fence.mbarrier_init.release.cluster;" ::: "memory");
            asm volatile("createpolicy.fractional.L2::evict_first.b64 %0, 1.0;" : "=l"(pol));
            for (int i = 0; i < NSLOT; ++i) issue(i);
            mbar_expect_tx(xqb, DH * 4);
            mbar_expect_tx(xob, DH * 2);
        }
        __syncwarp();
        asm volatile("bar.arrive 4, 64;" ::: "memory");
        cluster_arrive();
        cluster_wait();
        if (lane == 0) {
            volatile unsigned* prog = reinterpret_cast<volatile unsigned*>(sgen + OFF_PROG);
            volatile int* depth = reinterpret_cast<volatile int*>(sgen + OFF_DEPTH);
            for (int i = NSLOT; i < N_TILES; ++i) {
                mbar_wait(emptb + (i & (NSLOT - 1)) * 8, ((i >> 3) & 1) ^ 1);
                *prog = i - NSLOT + 1;
                if (i < T_WO0) {
                    unsigned n = 0;
                    while (true) {
                        const int D = *depth;
                        if (D >= NSLOT) break;
                        const int x = i - D;
                        if (mbar_test(emptb + (x & (NSLOT - 1)) * 8, (x >> 3) & 1)) break;
                        if (++n > SPIN_LIMIT) __trap();
                    }
                }
                if (i == T_WO0) {
                    unsigned n = 0;
                    while (*reinterpret_cast<volatile unsigned*>(sgen + OFF_GO) == 0) { if (++n > SPIN_LIMIT) __trap(); }
                }
                issue(i);
            }
        }
        __syncwarp();
        {
            const float* part = reinterpret_cast<const float*>(sgen + OFF_PART);
            const float* ml   = reinterpret_cast<const float*>(sgen + OFF_ML);
            uint32_t* obuf    = reinterpret_cast<uint32_t*>(sgen + OFF_OBUF);
            const float sc = 0.07216878364870322f * 1.4426950408889634f;
            const int u = lane & 7;
            const int pos0 = r * OB_STRIDE + 16 * (lane >> 4) + 4 * (u & 3) + 2 * ((lane >> 3) & 1) + (u >> 2);
            const uint32_t ra = mapa(sbase + OFF_OBUF + pos0 * 4, r ^ 1), rb = mapa(xob, r ^ 1);
            part_sync();
            const float4 ml0 = *reinterpret_cast<const float4*>(ml), ml1 = *reinterpret_cast<const float4*>(ml + 4);
            const float4 ml2 = *reinterpret_cast<const float4*>(ml + 8), ml3 = *reinterpret_cast<const float4*>(ml + 12);
            float2 pv[8][3];
#pragma unroll
            for (int w = 0; w < 8; ++w)
#pragma unroll
                for (int k = 0; k < 3; ++k) pv[w][k] = *reinterpret_cast<const float2*>(part + w * DH + 2 * (lane + 32 * k));
            const float mw[8] = {ml0.x, ml0.z, ml1.x, ml1.z, ml2.x, ml2.z, ml3.x, ml3.z};
            const float lw[8] = {ml0.y, ml0.w, ml1.y, ml1.w, ml2.y, ml2.w, ml3.y, ml3.w};
            const float M = fmaxf(fmaxf(fmaxf(mw[0], mw[1]), fmaxf(mw[2], mw[3])), fmaxf(fmaxf(mw[4], mw[5]), fmaxf(mw[6], mw[7])));
            float L = 0.f, o[3][2] = {{0.f, 0.f}, {0.f, 0.f}, {0.f, 0.f}};
#pragma unroll
            for (int w = 0; w < 8; ++w) {
                const float f = ex2((mw[w] - M) * sc);
                L = fmaf(f, lw[w], L);
#pragma unroll
                for (int k = 0; k < 3; ++k) {
                    o[k][0] = fmaf(f, pv[w][k].x, o[k][0]);
                    o[k][1] = fmaf(f, pv[w][k].y, o[k][1]);
                }
            }
            const float inv = rcp(L);
#pragma unroll
            for (int k = 0; k < 3; ++k) {
                const uint32_t ob = pack_bf16(o[k][0] * inv, o[k][1] * inv);
                obuf[pos0 + 32 * k] = ob;
                st_async_b32(ra + 128 * k, ob, rb);
            }
            __syncwarp();
            if (lane == 0) mbar_arrive(xob);
        }
    } else if (warp == 9) {
        cluster_arrive();
        cluster_wait();
        asm volatile("bar.sync 4, 64;" ::: "memory");
        if (lane == 0) {
            constexpr unsigned ADDS = PACE_TILES;
            volatile unsigned* prog = reinterpret_cast<volatile unsigned*>(sgen + OFF_PROG);
            volatile int* depth = reinterpret_cast<volatile int*>(sgen + OFF_DEPTH);
            const unsigned par = *reinterpret_cast<volatile unsigned*>(&g_epoch[br * 2 + r]) & 1u;
            unsigned* gp = &g_prog[par];
            if (blockIdx.x == 0) *reinterpret_cast<volatile unsigned*>(&g_prog[par ^ 1u]) = 0;
            unsigned reported = 0, n = 0;
            bool go = false;
            while (reported < ADDS) {
                unsigned cur = *prog;
                cur = cur < ADDS ? cur : ADDS;
                const unsigned delta = cur - reported;
                unsigned gsum;
                if (delta) {
                    asm volatile("atom.relaxed.gpu.global.add.u32 %0, [%1], %2;" : "=r"(gsum) : "l"(gp), "r"(delta) : "memory");
                    gsum += delta;
                } else {
                    asm volatile("ld.relaxed.gpu.global.u32 %0, [%1];" : "=r"(gsum) : "l"(gp) : "memory");
                }
                reported = cur;
                const int lead = (int)(reported * 128u) - (int)gsum;
                int D = PACE_D0 - ((PACE_SL * lead + 64) >> 7);
                *depth = D < PACE_DMIN ? PACE_DMIN : D;
                if (!go && gsum >= (ADDS - WO_GATE) * 128u) {
                    go = true;
                    *reinterpret_cast<volatile unsigned*>(sgen + OFF_GO) = 1;
                }
                if (++n > SPIN_LIMIT) __trap();
            }
            while (!go) {
                unsigned gsum;
                asm volatile("ld.relaxed.gpu.global.u32 %0, [%1];" : "=r"(gsum) : "l"(gp) : "memory");
                if (gsum >= (ADDS - WO_GATE) * 128u) break;
                if (++n > SPIN_LIMIT) __trap();
            }
            *reinterpret_cast<volatile unsigned*>(sgen + OFF_GO) = 1;
        }
    } else {
        const int g  = lane >> 2;
        const int t  = lane & 3;
        const int gs = warp >> 2;
        const int wi = warp & 3;
        const int grp = br * 2 + r;

        uint32_t xb[3][2];
        {
            const uint32_t* xw = reinterpret_cast<const uint32_t*>(p.x[br] + (g & 1) * DM + 320 * r + 16 * wi + 2 * t);
#pragma unroll
            for (int ii = 0; ii < 3; ++ii) {
                const int i = gs + 2 * ii;
                if (i < N_WQ) { xb[ii][0] = __ldg(xw + 32 * i); xb[ii][1] = __ldg(xw + 32 * i + 4); }
                else { xb[ii][0] = 0; xb[ii][1] = 0; }
            }
        }
        unsigned epoch = 0;
        if (tid == 0) epoch = *reinterpret_cast<volatile unsigned*>(&g_epoch[grp]);

        uint32_t koff[3], voff[3];
        {
            const int rowk = 16 * wi + (lane & 7) + 8 * ((lane >> 3) & 1), hik = lane >> 4;
            const int rowv = 16 * wi + (lane & 7) + 8 * (lane >> 4),       hiv = (lane >> 3) & 1;
#pragma unroll
            for (int sg = 0; sg < 3; ++sg) {
                const int lk = 3 * rowk + sg, lv = 3 * rowv + sg;
                koff[sg] = lk * 128 + ((hik ^ (lk & 7)) << 4);
                voff[sg] = lv * 128 + ((hiv ^ (lv & 7)) << 4);
            }
        }

        cluster_arrive();
        cluster_wait();

        float acc[12][4];
#pragma unroll
        for (int mt = 0; mt < 12; ++mt) { acc[mt][0] = acc[mt][1] = acc[mt][2] = acc[mt][3] = 0.f; }

#pragma unroll
        for (int ii = 0; ii < 3; ++ii) {
            const int i = gs + 2 * ii;
            if (i < N_WQ) {
                mbar_wait(fullb + i * 8, 0);
                pv_step(acc, ring + i * SLOT_BYTES, voff, xb[ii][0], xb[ii][1]);
                __syncwarp();
                if (lane == 0) mbar_arrive(emptb + i * 8);
            }
        }
        float* part = reinterpret_cast<float*>(sgen + OFF_PART);
        float* qown = reinterpret_cast<float*>(sgen + OFF_QOWN);
        float* qpeer = reinterpret_cast<float*>(sgen + OFF_QPEER);
        {
            float* dst = part + (warp * 2 + (t & 1)) * QP_STRIDE_B + g + 8 * (t >> 1);
#pragma unroll
            for (int mt = 0; mt < 12; ++mt) {
                const float v = sel4(t, acc[mt][0], acc[mt][1], acc[mt][2], acc[mt][3]);
                dst[16 * mt] = v;
            }
            if (tid == 0) *reinterpret_cast<unsigned*>(sgen + OFF_EPOCH) = epoch;
        }
        cons_sync();
        if (tid < DH) {
            float own = 0.f, oth = 0.f;
#pragma unroll
            for (int w = 0; w < 8; ++w) {
                own += part[(w * 2 + r) * QP_STRIDE_B + tid];
                oth += part[(w * 2 + (r ^ 1)) * QP_STRIDE_B + tid];
            }
            qown[tid] = own;
            st_async_b32(mapa(sbase + OFF_QPEER + tid * 4, r ^ 1), __float_as_uint(oth), mapa(xqb, r ^ 1));
        }
        cons_sync();
        mbar_wait_cluster(xqb, 0);
        epoch = *reinterpret_cast<volatile unsigned*>(sgen + OFF_EPOCH);

        uint32_t qb[12][2];
#pragma unroll
        for (int s = 0; s < 12; ++s) {
            const int c = 16 * s + 2 * t;
            qb[s][0] = pack_bf16(qown[c] + qpeer[c], qown[c + 1] + qpeer[c + 1]);
            qb[s][1] = pack_bf16(qown[c + 8] + qpeer[c + 8], qown[c + 9] + qpeer[c + 9]);
        }

        auto pub_addr = [&](int q) {
            const int o = (t & 1) * 320 + 16 * (warp + 8 * q) + g + 8 * (t >> 1);
            const int red = (o * 3277) >> 16;
            return g_part + ((size_t)(grp * NH + red) * NH + h) * 20 + (o - 20 * red);
        };
#pragma unroll
        for (int q = 0; q < 3; ++q)
            if (q < 2 || warp < 4)
                asm volatile("st.relaxed.gpu.global.b64 [%0], %1;" ::"l"(pub_addr(q)), "l"((unsigned long long)epoch << 32) : "memory");
        if (tid < 160 && (tid & 7) == 0) {
            const int oq = 20 * h + (tid >> 3);
            p.out[(oq >= 320 ? 2 * DM - 320 : 0) + br * DM + r * 320 + oq] = __float2bfloat16(0.f);
        }
#pragma unroll
        for (int mt = 0; mt < 12; ++mt) { acc[mt][0] = acc[mt][1] = acc[mt][2] = acc[mt][3] = 0.f; }
        const float sc = 0.07216878364870322f * 1.4426950408889634f;
        float m = -INFINITY, l = 0.f;

#pragma unroll 1
        for (int jj = 0; jj < N_PAIR / 2; ++jj) {
            const int iK = T_KV0 + 2 * (2 * jj + gs);
            const int iV = iK + 1;
            const int sK = iK & (NSLOT - 1), sV = iV & (NSLOT - 1);

            mbar_wait(fullb + sK * 8, (iK >> 3) & 1);
            float cA[4] = {0.f, 0.f, 0.f, 0.f}, cB[4] = {0.f, 0.f, 0.f, 0.f};
            {
                const uint32_t kt = ring + sK * SLOT_BYTES;
#pragma unroll
                for (int s = 0; s < 12; s += 2) {
                    uint32_t a0[4], a1[4];
                    ldsm4(a0, (kt + koff[s >> 2]) ^ ((s & 3) << 5));
                    ldsm4(a1, (kt + koff[(s + 1) >> 2]) ^ (((s + 1) & 3) << 5));
                    mma16816(cA, a0, qb[s][0], qb[s][1]);
                    mma16816(cB, a1, qb[s + 1][0], qb[s + 1][1]);
                }
            }
            __syncwarp();
            if (lane == 0) mbar_arrive(emptb + sK * 8);

            const float s0 = cA[0] + cB[0];
            const float s1 = cA[2] + cB[2];
            float bm = fmaxf(s0, s1);
            bm = fmaxf(bm, __shfl_xor_sync(0xffffffffu, bm, 4));
            bm = fmaxf(bm, __shfl_xor_sync(0xffffffffu, bm, 8));
            bm = fmaxf(bm, __shfl_xor_sync(0xffffffffu, bm, 16));
            if (bm > m) {
                const float f = ex2((m - bm) * sc);
                l *= f;
#pragma unroll
                for (int mt = 0; mt < 12; ++mt) { acc[mt][0] *= f; acc[mt][2] *= f; }
                m = bm;
            }
            const float ms = m * sc;
            const float p0 = ex2(fmaf(s0, sc, -ms));
            const float p1 = ex2(fmaf(s1, sc, -ms));
            l += p0 + p1;
            const uint32_t pk = pack_bf16(p0, p1);
            const uint32_t u = __shfl_sync(0xffffffffu, pk, 8 * t);
            const uint32_t v = __shfl_sync(0xffffffffu, pk, 8 * t + 4);
            const uint32_t b0 = __byte_perm(u, v, 0x5410);
            const uint32_t b1 = __byte_perm(u, v, 0x7632);

            mbar_wait(fullb + sV * 8, (iV >> 3) & 1);
            pv_step(acc, ring + sV * SLOT_BYTES, voff, b0, b1);
            __syncwarp();
            if (lane == 0) mbar_arrive(emptb + sV * 8);
        }

        l += __shfl_xor_sync(0xffffffffu, l, 4);
        l += __shfl_xor_sync(0xffffffffu, l, 8);
        l += __shfl_xor_sync(0xffffffffu, l, 16);
        float* ml = reinterpret_cast<float*>(sgen + OFF_ML);
        if (t < 2) {
            float* dst = part + warp * DH + g + 8 * t;
#pragma unroll
            for (int mt = 0; mt < 12; ++mt) dst[16 * mt] = t ? acc[mt][2] : acc[mt][0];
        }
        if (lane == 0) { ml[warp * 2] = m; ml[warp * 2 + 1] = l; }
        part_arrive();

        unsigned long long* pub[3];
#pragma unroll
        for (int q = 0; q < 3; ++q) {
            pub[q] = pub_addr(q);
            asm volatile("" : "+l"(pub[q]));
        }
        const unsigned long long* src = g_part + (size_t)(grp * NH + h) * 640 + tid;
        const int oj = 20 * h + (tid >> 3);
        __nv_bfloat16* dsto = p.out + (oj >= 320 ? 2 * DM - 320 : 0) + br * DM + r * 320 + oj;
        asm volatile("" : "+l"(src), "+l"(dsto));

        uint32_t woff[3][2];
        {
            const int rowt = (lane & 7) + 8 * (lane >> 4), hit = (lane >> 3) & 1;
#pragma unroll
            for (int q = 0; q < 3; ++q) {
                const int mt = warp + 8 * q;
#pragma unroll
                for (int kk = 0; kk < 2; ++kk) {
                    const int line = 5 * (16 * kk + rowt) + (mt >> 2);
                    woff[q][kk] = ring + line * 128 + (((2 * (mt & 3) + hit) ^ (line & 7)) << 4);
                }
            }
        }
        mbar_wait_cluster(xob, 0);
        float oc[3][2][4];
#pragma unroll
        for (int q = 0; q < 3; ++q)
#pragma unroll
            for (int kk = 0; kk < 2; ++kk) { oc[q][kk][0] = oc[q][kk][1] = oc[q][kk][2] = oc[q][kk][3] = 0.f; }
        {
            const uint32_t* obuf = reinterpret_cast<const uint32_t*>(sgen + OFF_OBUF);
            const uint4* os = reinterpret_cast<const uint4*>(obuf + (g & 1) * OB_STRIDE + 4 * t);
            uint4 b[N_WO];
#pragma unroll
            for (int i = 0; i < N_WO; ++i) b[i] = os[4 * i];
            uint32_t a[2][3][2][4];
            const bool three = warp < 4;
#pragma unroll
            for (int i = 0; i <= N_WO; ++i) {
                if (i < N_WO) {
                    const uint32_t so = ((T_WO0 + i) & (NSLOT - 1)) * SLOT_BYTES;
                    mbar_wait(wob + i * 8, 0);
#pragma unroll
                    for (int q = 0; q < 2; ++q) {
                        ldsm4t(a[i & 1][q][0], woff[q][0] + so);
                        ldsm4t(a[i & 1][q][1], woff[q][1] + so);
                    }
                    if (three) { ldsm4t(a[i & 1][2][0], woff[2][0] + so); ldsm4t(a[i & 1][2][1], woff[2][1] + so); }
                }
                if (i > 0) {
                    const int j = i - 1;
#pragma unroll
                    for (int q = 0; q < 2; ++q) {
                        mma16816(oc[q][0], a[j & 1][q][0], b[j].x, b[j].y);
                        mma16816(oc[q][1], a[j & 1][q][1], b[j].z, b[j].w);
                    }
                    if (three) {
                        mma16816(oc[2][0], a[j & 1][2][0], b[j].x, b[j].y);
                        mma16816(oc[2][1], a[j & 1][2][1], b[j].z, b[j].w);
                    }
                }
            }
        }
        const unsigned tag = epoch + 1u;
#pragma unroll
        for (int q = 0; q < 3; ++q) {
            const float v = sel4(t, oc[q][0][0] + oc[q][1][0], oc[q][0][1] + oc[q][1][1],
                                    oc[q][0][2] + oc[q][1][2], oc[q][0][3] + oc[q][1][3]);
            const unsigned long long w = ((unsigned long long)tag << 32) | __float_as_uint(v);
            if (q < 2 || warp < 4)
                asm volatile("st.relaxed.gpu.global.b64 [%0], %1;" ::"l"(pub[q]), "l"(w) : "memory");
        }
        if (tid < 160) {
            float v[4] = {0.f, 0.f, 0.f, 0.f};
            {
                unsigned n = 0;
                bool have[4] = {false, false, false, false};
                while (true) {
                    unsigned long long w[4] = {0ull, 0ull, 0ull, 0ull};
#pragma unroll
                    for (int i = 0; i < 4; ++i)
                        if (!have[i]) asm volatile("ld.relaxed.gpu.global.b64 %0, [%1];" : "=l"(w[i]) : "l"(src + i * 160) : "memory");
#pragma unroll
                    for (int i = 0; i < 4; ++i)
                        if (!have[i] && (unsigned)(w[i] >> 32) == tag) { have[i] = true; v[i] = __uint_as_float((unsigned)w[i]); }
                    if (__all_sync(0xffffffffu, have[0] && have[1] && have[2] && have[3])) break;
                    if (++n > SPIN_LIMIT) __trap();
                }
            }
            float* red = reinterpret_cast<float*>(sgen + OFF_PART);
#pragma unroll
            for (int i = 0; i < 4; ++i) red[tid + 160 * i] = v[i];
            asm volatile("bar.sync 3, 160;" ::: "memory");
            const int j = tid >> 3, s = tid & 7;
#pragma unroll
            for (int i = 0; i < 4; ++i) v[i] = red[(4 * s + i) * 20 + j];
            float sum = (v[0] + v[1]) + (v[2] + v[3]);
            sum += __shfl_xor_sync(0xffffffffu, sum, 1);
            sum += __shfl_xor_sync(0xffffffffu, sum, 2);
            sum += __shfl_xor_sync(0xffffffffu, sum, 4);
            if (s == 0) *dsto = __float2bfloat16(sum);
            if (h == 0 && tid == 0) *reinterpret_cast<volatile unsigned*>(&g_epoch[grp]) = tag;
        }
    }
}

typedef CUresult (*EncodeTiledFn)(CUtensorMap*, CUtensorMapDataType, cuuint32_t, void*, const cuuint64_t*,
                                  const cuuint64_t*, const cuuint32_t*, const cuuint32_t*, CUtensorMapInterleave,
                                  CUtensorMapSwizzle, CUtensorMapL2promotion, CUtensorMapFloatOOBfill);

bool encode(EncodeTiledFn fn, CUtensorMap* tm, const void* ptr, int rank, const cuuint64_t* dims,
            const cuuint64_t* strides, const cuuint32_t* box) {
    const cuuint32_t es[3] = {1, 1, 1};
    CUresult rc = fn(tm, CU_TENSOR_MAP_DATA_TYPE_BFLOAT16, (cuuint32_t)rank, const_cast<void*>(ptr), dims, strides, box, es,
                     CU_TENSOR_MAP_INTERLEAVE_NONE, CU_TENSOR_MAP_SWIZZLE_128B, CU_TENSOR_MAP_L2_PROMOTION_L2_128B,
                     CU_TENSOR_MAP_FLOAT_OOB_FILL_NONE);
    if (rc != CUDA_SUCCESS) { fprintf(stderr, "cuTensorMapEncodeTiled failed: %d\n", (int)rc); return false; }
    return true;
}


}

extern "C" void kernel_launch(void* const* d_in, const int* in_sizes, int n_in, void* d_out, int out_size) {
    (void)in_sizes; (void)n_in; (void)out_size;
    static EncodeTiledFn fn = nullptr;
    if (!fn) {
        void* f = nullptr;
        cudaDriverEntryPointQueryResult qr;
        if (cudaGetDriverEntryPoint("cuTensorMapEncodeTiled", &f, cudaEnableDefault, &qr) != cudaSuccess || !f) {
            fprintf(stderr, "cuTensorMapEncodeTiled not available\n");
            return;
        }
        fn = (EncodeTiledFn)f;
        cudaFuncSetAttribute(fused_decode_kernel, cudaFuncAttributeMaxDynamicSharedMemorySize, SMEM_BYTES);
    }
    Params p;
    for (int b = 0; b < 2; ++b) {
        void* const* in = d_in + 5 * b;
        p.x[b] = (const __nv_bfloat16*)in[0];
        p.kraw[b] = (const __nv_bfloat16*)in[1]; p.wqraw[b] = (const __nv_bfloat16*)in[3];
        {
            const cuuint64_t dims[2] = {64, (cuuint64_t)2 * NH * SK * 3};
            const cuuint64_t strides[1] = {128};
            const cuuint32_t box[2] = {64, 192};
            if (!encode(fn, &p.k[b], in[1], 2, dims, strides, box)) return;
            if (!encode(fn, &p.v[b], in[2], 2, dims, strides, box)) return;
        }
        {
            const cuuint64_t dims[3] = {64, 96, 640};
            const cuuint64_t strides[2] = {128, 12288};
            const cuuint32_t box[3] = {64, 3, 64};
            if (!encode(fn, &p.wq[b], in[3], 3, dims, strides, box)) return;
        }
        {
            const cuuint64_t dims[3] = {64, 10, 6144};
            const cuuint64_t strides[2] = {128, 1280};
            const cuuint32_t box[3] = {64, 5, 32};
            if (!encode(fn, &p.wo[b], in[4], 3, dims, strides, box)) return;
        }
    }
    p.out = (__nv_bfloat16*)d_out;
    fused_decode_kernel<<<128, NTHREADS, SMEM_BYTES>>>(p);
}
```
